```python
import torch

def _softmax(x, axis=-1):
    return torch.softmax(x, dim=axis)

def _gelu(x):
    return torch.nn.functional.gelu(x, approximate='tanh')

def _silu(x):
    return torch.nn.functional.silu(x)

def _sigmoid(x):
    return torch.sigmoid(x)

def _layernorm(x, axis=-1, eps=1e-05):
    m = x.mean(dim=axis, keepdim=True)
    v = x.var(dim=axis, keepdim=True, unbiased=False)
    return (x - m) / torch.sqrt(v + eps)

def _scatter_add(tgt, idx, src, axis=0):
    return tgt.clone().index_add_(axis, idx, src)

def _segment_sum(src, seg, n):
    out = torch.zeros((n,) + src.shape[1:], dtype=src.dtype)
    return out.index_add_(0, seg, src)

def _pad(x, pw):
    flat = tuple((v for pair in reversed(pw) for v in pair))
    return torch.nn.functional.pad(x, flat)
kernel_name = 'gated_mix__grouped_kv_mqa__mixer_gmlp__prompt'

def setup_inputs():

    _w = lambda a: (lambda t: t.to(torch.bfloat16) if t.is_floating_point() else t)(torch.as_tensor(a))

    def _A_setup():
        B, S, D, H = (1, 2048, 640, 32)
        Dh = D // H
        return {'x': _w((lambda *s: torch.randn(*s, dtype=torch.bfloat16) * 0.05)(B, S, D)), 'wq': _w((lambda *s: torch.randn(*s, dtype=torch.bfloat16) * 1.6)(D, H * Dh)), 'wk': _w((lambda *s: torch.randn(*s, dtype=torch.bfloat16) * 1.6)(D, Dh)), 'wv': _w((lambda *s: torch.randn(*s, dtype=torch.bfloat16) * 0.2)(D, Dh)), 'wo': _w((lambda *s: torch.randn(*s, dtype=torch.bfloat16) * 0.2)(H * Dh, D))}
    _A_in = _A_setup()

    def _B_setup():
        B, S, D, F = (1, 2048, 640, 1728)
        Fh = F // 2
        return {'x': _w((lambda *s: torch.randn(*s, dtype=torch.bfloat16) * 0.05)(B, S, D)), 'w_in': _w((lambda *s: torch.randn(*s, dtype=torch.bfloat16) * 0.8)(D, 2 * Fh)), 'w_sp': _w(0.01 * (lambda *s: torch.randn(*s, dtype=torch.bfloat16) * 0.8)(S, S)), 'b_sp': _w(1.0 + 0.01 * (lambda *s: torch.randn(*s, dtype=torch.bfloat16) * 0.05)(S)), 'w_out': _w((lambda *s: torch.randn(*s, dtype=torch.bfloat16) * 0.05)(Fh, D))}
    _B_in = _B_setup()
    return {'A_x': _A_in['x'], 'A_wq': _A_in['wq'], 'A_wk': _A_in['wk'], 'A_wv': _A_in['wv'], 'A_wo': _A_in['wo'], 'B_x': _B_in['x'], 'B_w_in': _B_in['w_in'], 'B_w_sp': _B_in['w_sp'], 'B_b_sp': _B_in['b_sp'], 'B_w_out': _B_in['w_out'], 'gate_w': _w((lambda *s: torch.randn(*s, dtype=torch.bfloat16) * 0.05)(640) * 16.0)}

def reference(A_x, A_wq, A_wk, A_wv, A_wo, B_x, B_w_in, B_w_sp, B_b_sp, B_w_out, gate_w):

    def _A_ref(x, wq, wk, wv, wo):
        B, S, D = x.shape
        H = 32
        Dh = D // H
        q = (lambda x, *d: x.permute(*d))((x @ wq).reshape(B, S, H, Dh), 0, 2, 1, 3)
        k = x @ wk
        v = x @ wv
        scores = torch.einsum('bhqd,bkd->bhqk', q, k) * Dh ** (-0.5)
        p = _softmax(scores, axis=-1)
        o = torch.einsum('bhqk,bkd->bhqd', p, v)
        return (lambda x, *d: x.permute(*d))(o, 0, 2, 1, 3).reshape(B, S, H * Dh) @ wo

    def _B_ref(x, w_in, w_sp, b_sp, w_out):
        B, S, D = x.shape
        F = w_in.shape[-1]
        Fh = F // 2
        z = _gelu(torch.einsum('bsd,df->bsf', x, w_in))
        z1 = z[..., :Fh].clone()
        z2 = _layernorm(z[..., Fh:], axis=-1)
        g = torch.einsum('ts,bsf->btf', w_sp, z2) + b_sp[None, :, None]
        return torch.einsum('bsf,fd->bsd', z1 * g, w_out)
    x = A_x
    g = _sigmoid((x * gate_w).sum(-1, keepdims=True))
    a = _A_ref(x, A_wq, A_wk, A_wv, A_wo)
    b = _B_ref(x, B_w_in, B_w_sp, B_b_sp, B_w_out)
    return g * a + (1 - g) * b
```

```cpp
#include <cuda_runtime.h>
#include <cuda_bf16.h>
#include <cuda.h>
#include <stdint.h>

namespace {

constexpr int S_LEN = 2048, DM = 640, FH = 864;
constexpr int NCTA = 128;
#define PAT8 0xB5u
constexpr uint32_t PAT = PAT8 * 0x101u;
#define GBATCH 2
constexpr int GST = 4;
constexpr int GST_BYTES = 36864;
constexpr int KST = 4;
constexpr int KST_BYTES = 12288;
constexpr int QS_PITCH = 168;
constexpr int SM_G = 0;
constexpr int SM_KV = SM_G + GST * GST_BYTES;
constexpr int SM_Q = SM_KV + KST * KST_BYTES;
constexpr int SM_MISC = SM_Q + 64 * QS_PITCH * 2;
constexpr int SM_TOTAL = SM_MISC + 2048 + 1024;

constexpr int F_KV = 0, F_DONE = 1, F_W2 = 2, F_WR = 3, F_W1 = 4, F_STAT = 5, F_Z2 = F_STAT + 32, F_H = F_Z2 + 128, F_O = F_H + 32, F_NUM = F_O + 64;

__device__ __align__(1024) uint8_t g_kv[16 * KST_BYTES];
__device__ __align__(1024) uint8_t g_z2n[4 * 32 * 27648];
__device__ __align__(1024) uint8_t g_hp[32 * 108 * 1024];
__device__ __align__(1024) uint8_t g_op[32 * 80 * 1024];
__device__ __align__(1024) uint8_t g_wint[8 * 80 * 3456];
__device__ __align__(1024) uint8_t g_wot[4 * 80 * 2560];
__device__ __align__(1024) uint8_t g_woutt[4 * 108 * 2560];
__device__ uint4 g_z1[NCTA * 14 * 128];
__device__ float2 g_part[32 * 4 * 64];
__device__ __align__(128) float g_kvmax[64];
__device__ __align__(128) float g_gate[S_LEN];
__device__ unsigned g_flags[F_NUM * 8];
__device__ uint32_t g_const[4] = {0u, 0u, 0x3F003F00u, 0u};

struct Params {
    CUtensorMap mx, mwsp, mwq;
    const __nv_bfloat16 *x, *wk, *wv, *bsp, *gw, *wsp, *wo, *wout, *win;
    __nv_bfloat16* out;
};

template<int TB> __device__ __forceinline__ void wgmma_rs_n24(float (&d)[12], uint32_t a0, uint32_t a1, uint32_t a2, uint32_t a3, uint64_t db, int scale_d) {
  asm volatile("{\n.reg .pred p;\nsetp.ne.b32 p, %17, 0;\nwgmma.mma_async.sync.aligned.m64n24k16.f32.bf16.bf16 {%0,%1,%2,%3,%4,%5,%6,%7,%8,%9,%10,%11}, {%12,%13,%14,%15}, %16, p, 1, 1, %18;\n}"
    : "+f"(d[0]), "+f"(d[1]), "+f"(d[2]), "+f"(d[3]), "+f"(d[4]), "+f"(d[5]), "+f"(d[6]), "+f"(d[7]), "+f"(d[8]), "+f"(d[9]), "+f"(d[10]), "+f"(d[11])
    : "r"(a0), "r"(a1), "r"(a2), "r"(a3), "l"(db), "r"(scale_d), "n"(TB));
}
template<int TB> __device__ __forceinline__ void wgmma_rs_n64(float (&d)[32], uint32_t a0, uint32_t a1, uint32_t a2, uint32_t a3, uint64_t db, int scale_d) {
  asm volatile("{\n.reg .pred p;\nsetp.ne.b32 p, %37, 0;\nwgmma.mma_async.sync.aligned.m64n64k16.f32.bf16.bf16 {%0,%1,%2,%3,%4,%5,%6,%7,%8,%9,%10,%11,%12,%13,%14,%15,%16,%17,%18,%19,%20,%21,%22,%23,%24,%25,%26,%27,%28,%29,%30,%31}, {%32,%33,%34,%35}, %36, p, 1, 1, %38;\n}"
    : "+f"(d[0]), "+f"(d[1]), "+f"(d[2]), "+f"(d[3]), "+f"(d[4]), "+f"(d[5]), "+f"(d[6]), "+f"(d[7]), "+f"(d[8]), "+f"(d[9]), "+f"(d[10]), "+f"(d[11]), "+f"(d[12]), "+f"(d[13]), "+f"(d[14]), "+f"(d[15]), "+f"(d[16]), "+f"(d[17]), "+f"(d[18]), "+f"(d[19]), "+f"(d[20]), "+f"(d[21]), "+f"(d[22]), "+f"(d[23]), "+f"(d[24]), "+f"(d[25]), "+f"(d[26]), "+f"(d[27]), "+f"(d[28]), "+f"(d[29]), "+f"(d[30]), "+f"(d[31])
    : "r"(a0), "r"(a1), "r"(a2), "r"(a3), "l"(db), "r"(scale_d), "n"(TB));
}
template<int TA, int TB> __device__ __forceinline__ void wgmma_ss_n24(float (&d)[12], uint64_t da, uint64_t db, int scale_d) {
  asm volatile("{\n.reg .pred p;\nsetp.ne.b32 p, %14, 0;\nwgmma.mma_async.sync.aligned.m64n24k16.f32.bf16.bf16 {%0,%1,%2,%3,%4,%5,%6,%7,%8,%9,%10,%11}, %12, %13, p, 1, 1, %15, %16;\n}"
    : "+f"(d[0]), "+f"(d[1]), "+f"(d[2]), "+f"(d[3]), "+f"(d[4]), "+f"(d[5]), "+f"(d[6]), "+f"(d[7]), "+f"(d[8]), "+f"(d[9]), "+f"(d[10]), "+f"(d[11])
    : "l"(da), "l"(db), "r"(scale_d), "n"(TA), "n"(TB));
}
template<int TA, int TB> __device__ __forceinline__ void wgmma_ss_n64(float (&d)[32], uint64_t da, uint64_t db, int scale_d) {
  asm volatile("{\n.reg .pred p;\nsetp.ne.b32 p, %34, 0;\nwgmma.mma_async.sync.aligned.m64n64k16.f32.bf16.bf16 {%0,%1,%2,%3,%4,%5,%6,%7,%8,%9,%10,%11,%12,%13,%14,%15,%16,%17,%18,%19,%20,%21,%22,%23,%24,%25,%26,%27,%28,%29,%30,%31}, %32, %33, p, 1, 1, %35, %36;\n}"
    : "+f"(d[0]), "+f"(d[1]), "+f"(d[2]), "+f"(d[3]), "+f"(d[4]), "+f"(d[5]), "+f"(d[6]), "+f"(d[7]), "+f"(d[8]), "+f"(d[9]), "+f"(d[10]), "+f"(d[11]), "+f"(d[12]), "+f"(d[13]), "+f"(d[14]), "+f"(d[15]), "+f"(d[16]), "+f"(d[17]), "+f"(d[18]), "+f"(d[19]), "+f"(d[20]), "+f"(d[21]), "+f"(d[22]), "+f"(d[23]), "+f"(d[24]), "+f"(d[25]), "+f"(d[26]), "+f"(d[27]), "+f"(d[28]), "+f"(d[29]), "+f"(d[30]), "+f"(d[31])
    : "l"(da), "l"(db), "r"(scale_d), "n"(TA), "n"(TB));
}
template<int TA, int TB> __device__ __forceinline__ void wgmma_ss_n88(float (&d)[44], uint64_t da, uint64_t db, int scale_d) {
  asm volatile("{\n.reg .pred p;\nsetp.ne.b32 p, %46, 0;\nwgmma.mma_async.sync.aligned.m64n88k16.f32.bf16.bf16 {%0,%1,%2,%3,%4,%5,%6,%7,%8,%9,%10,%11,%12,%13,%14,%15,%16,%17,%18,%19,%20,%21,%22,%23,%24,%25,%26,%27,%28,%29,%30,%31,%32,%33,%34,%35,%36,%37,%38,%39,%40,%41,%42,%43}, %44, %45, p, 1, 1, %47, %48;\n}"
    : "+f"(d[0]), "+f"(d[1]), "+f"(d[2]), "+f"(d[3]), "+f"(d[4]), "+f"(d[5]), "+f"(d[6]), "+f"(d[7]), "+f"(d[8]), "+f"(d[9]), "+f"(d[10]), "+f"(d[11]), "+f"(d[12]), "+f"(d[13]), "+f"(d[14]), "+f"(d[15]), "+f"(d[16]), "+f"(d[17]), "+f"(d[18]), "+f"(d[19]), "+f"(d[20]), "+f"(d[21]), "+f"(d[22]), "+f"(d[23]), "+f"(d[24]), "+f"(d[25]), "+f"(d[26]), "+f"(d[27]), "+f"(d[28]), "+f"(d[29]), "+f"(d[30]), "+f"(d[31]), "+f"(d[32]), "+f"(d[33]), "+f"(d[34]), "+f"(d[35]), "+f"(d[36]), "+f"(d[37]), "+f"(d[38]), "+f"(d[39]), "+f"(d[40]), "+f"(d[41]), "+f"(d[42]), "+f"(d[43])
    : "l"(da), "l"(db), "r"(scale_d), "n"(TA), "n"(TB));
}
template<int TA, int TB> __device__ __forceinline__ void wgmma_ss_n96(float (&d)[48], uint64_t da, uint64_t db, int scale_d) {
  asm volatile("{\n.reg .pred p;\nsetp.ne.b32 p, %50, 0;\nwgmma.mma_async.sync.aligned.m64n96k16.f32.bf16.bf16 {%0,%1,%2,%3,%4,%5,%6,%7,%8,%9,%10,%11,%12,%13,%14,%15,%16,%17,%18,%19,%20,%21,%22,%23,%24,%25,%26,%27,%28,%29,%30,%31,%32,%33,%34,%35,%36,%37,%38,%39,%40,%41,%42,%43,%44,%45,%46,%47}, %48, %49, p, 1, 1, %51, %52;\n}"
    : "+f"(d[0]), "+f"(d[1]), "+f"(d[2]), "+f"(d[3]), "+f"(d[4]), "+f"(d[5]), "+f"(d[6]), "+f"(d[7]), "+f"(d[8]), "+f"(d[9]), "+f"(d[10]), "+f"(d[11]), "+f"(d[12]), "+f"(d[13]), "+f"(d[14]), "+f"(d[15]), "+f"(d[16]), "+f"(d[17]), "+f"(d[18]), "+f"(d[19]), "+f"(d[20]), "+f"(d[21]), "+f"(d[22]), "+f"(d[23]), "+f"(d[24]), "+f"(d[25]), "+f"(d[26]), "+f"(d[27]), "+f"(d[28]), "+f"(d[29]), "+f"(d[30]), "+f"(d[31]), "+f"(d[32]), "+f"(d[33]), "+f"(d[34]), "+f"(d[35]), "+f"(d[36]), "+f"(d[37]), "+f"(d[38]), "+f"(d[39]), "+f"(d[40]), "+f"(d[41]), "+f"(d[42]), "+f"(d[43]), "+f"(d[44]), "+f"(d[45]), "+f"(d[46]), "+f"(d[47])
    : "l"(da), "l"(db), "r"(scale_d), "n"(TA), "n"(TB));
}
template<int TA, int TB> __device__ __forceinline__ void wgmma_ss_n128(float (&d)[64], uint64_t da, uint64_t db, int scale_d) {
  asm volatile("{\n.reg .pred p;\nsetp.ne.b32 p, %66, 0;\nwgmma.mma_async.sync.aligned.m64n128k16.f32.bf16.bf16 {%0,%1,%2,%3,%4,%5,%6,%7,%8,%9,%10,%11,%12,%13,%14,%15,%16,%17,%18,%19,%20,%21,%22,%23,%24,%25,%26,%27,%28,%29,%30,%31,%32,%33,%34,%35,%36,%37,%38,%39,%40,%41,%42,%43,%44,%45,%46,%47,%48,%49,%50,%51,%52,%53,%54,%55,%56,%57,%58,%59,%60,%61,%62,%63}, %64, %65, p, 1, 1, %67, %68;\n}"
    : "+f"(d[0]), "+f"(d[1]), "+f"(d[2]), "+f"(d[3]), "+f"(d[4]), "+f"(d[5]), "+f"(d[6]), "+f"(d[7]), "+f"(d[8]), "+f"(d[9]), "+f"(d[10]), "+f"(d[11]), "+f"(d[12]), "+f"(d[13]), "+f"(d[14]), "+f"(d[15]), "+f"(d[16]), "+f"(d[17]), "+f"(d[18]), "+f"(d[19]), "+f"(d[20]), "+f"(d[21]), "+f"(d[22]), "+f"(d[23]), "+f"(d[24]), "+f"(d[25]), "+f"(d[26]), "+f"(d[27]), "+f"(d[28]), "+f"(d[29]), "+f"(d[30]), "+f"(d[31]), "+f"(d[32]), "+f"(d[33]), "+f"(d[34]), "+f"(d[35]), "+f"(d[36]), "+f"(d[37]), "+f"(d[38]), "+f"(d[39]), "+f"(d[40]), "+f"(d[41]), "+f"(d[42]), "+f"(d[43]), "+f"(d[44]), "+f"(d[45]), "+f"(d[46]), "+f"(d[47]), "+f"(d[48]), "+f"(d[49]), "+f"(d[50]), "+f"(d[51]), "+f"(d[52]), "+f"(d[53]), "+f"(d[54]), "+f"(d[55]), "+f"(d[56]), "+f"(d[57]), "+f"(d[58]), "+f"(d[59]), "+f"(d[60]), "+f"(d[61]), "+f"(d[62]), "+f"(d[63])
    : "l"(da), "l"(db), "r"(scale_d), "n"(TA), "n"(TB));
}

__device__ __forceinline__ uint64_t mkdesc(uint32_t lo, uint32_t hi) { uint64_t d; asm("mov.b64 %0, {%1, %2};" : "=l"(d) : "r"(lo), "r"(hi)); return d; }
__device__ __forceinline__ void mbar_init(uint32_t a, int c) { asm volatile("mbarrier.init.shared::cta.b64 [%0], %1;" :: "r"(a), "r"(c)); }
__device__ __forceinline__ void mbar_expect(uint32_t a, uint32_t b) { asm volatile("mbarrier.arrive.expect_tx.shared::cta.b64 _, [%0], %1;" :: "r"(a), "r"(b) : "memory"); }
__device__ __forceinline__ void mbar_arrive(uint32_t a) { asm volatile("mbarrier.arrive.shared::cta.b64 _, [%0];" :: "r"(a) : "memory"); }
#define TRACE(i)
#define TRW(i)
#define TR2(k, i)
#define SPIN_LIMIT (1 << 22)
#define SPIN_FAIL(code) __trap()
__device__ __forceinline__ void mbar_wait(uint32_t a, uint32_t ph) {
    asm volatile("{\n.reg .pred p, q;\n.reg .u32 c;\nmov.u32 c, 0;\n"
                 "W0:\nmbarrier.try_wait.parity.shared::cta.b64 p, [%0], %1;\n@p bra W1;\n"
                 "add.u32 c, c, 1;\nsetp.lt.u32 q, c, %2;\n@q bra W0;\ntrap;\n"
                 "W1:\n}" :: "r"(a), "r"(ph), "n"(SPIN_LIMIT) : "memory");
}
__device__ __forceinline__ uint32_t mbar_try(uint32_t a, uint32_t ph) {
    uint32_t ok;
    asm volatile("{\n.reg .pred p;\nmbarrier.test_wait.parity.shared::cta.b64 p, [%1], %2;\nselp.u32 %0, 1, 0, p;\n}" : "=r"(ok) : "r"(a), "r"(ph) : "memory");
    return ok;
}
__device__ __forceinline__ void wg_fence() { asm volatile("wgmma.fence.sync.aligned;" ::: "memory"); }
__device__ __forceinline__ void wg_commit() { asm volatile("wgmma.commit_group.sync.aligned;" ::: "memory"); }
template<int N> __device__ __forceinline__ void wg_wait() { asm volatile("wgmma.wait_group.sync.aligned %0;" :: "n"(N) : "memory"); }
__device__ __forceinline__ void bar_sync(int id, int n) { asm volatile("bar.sync %0, %1;" :: "r"(id), "r"(n) : "memory"); }
__device__ __forceinline__ void bar_arrive(int id, int n) { asm volatile("bar.arrive %0, %1;" :: "r"(id), "r"(n) : "memory"); }
__device__ __forceinline__ void fence_async() { asm volatile("fence.proxy.async;" ::: "memory"); }
__device__ __forceinline__ void flag_wait(int f, unsigned target) {
    const unsigned* p = &g_flags[f * 8];
    unsigned v;
    #pragma unroll 1
    for (int it = 0; it < SPIN_LIMIT; it++) {
        asm volatile("ld.acquire.gpu.global.u32 %0, [%1];" : "=r"(v) : "l"(p) : "memory");
        if (v >= target) return;
        __nanosleep(20);
    }
    SPIN_FAIL(f);
}
__device__ __forceinline__ void flag_add(int f) { asm volatile("red.release.gpu.global.add.u32 [%0], 1;" :: "l"(&g_flags[f * 8]) : "memory"); }
__device__ __forceinline__ void tma2d(uint32_t dst, const CUtensorMap* m, int c0, int c1, uint32_t bar) {
    asm volatile("cp.async.bulk.tensor.2d.shared::cluster.global.mbarrier::complete_tx::bytes [%0], [%1, {%3, %4}], [%2];"
        :: "r"(dst), "l"(m), "r"(bar), "r"(c0), "r"(c1) : "memory");
}
__device__ __forceinline__ void bulk_ld(uint32_t dst, const void* src, uint32_t bytes, uint32_t bar) {
    asm volatile("cp.async.bulk.shared::cluster.global.mbarrier::complete_tx::bytes [%0], [%1], %2, [%3];"
        :: "r"(dst), "l"(src), "r"(bytes), "r"(bar) : "memory");
}
__device__ __forceinline__ void tma2d_mc(uint32_t dst, const CUtensorMap* m, int c0, int c1, uint32_t bar) {
    asm volatile("cp.async.bulk.tensor.2d.shared::cluster.global.mbarrier::complete_tx::bytes.multicast::cluster [%0], [%1, {%3, %4}], [%2], %5;"
        :: "r"(dst), "l"(m), "r"(bar), "r"(c0), "r"(c1), "h"((uint16_t)3) : "memory");
}
__device__ __forceinline__ void bulk_ld_mc(uint32_t dst, const void* src, uint32_t bytes, uint32_t bar) {
    asm volatile("cp.async.bulk.shared::cluster.global.mbarrier::complete_tx::bytes.multicast::cluster [%0], [%1], %2, [%3], %4;"
        :: "r"(dst), "l"(src), "r"(bytes), "r"(bar), "h"((uint16_t)3) : "memory");
}
__device__ __forceinline__ void release2(uint32_t a, uint32_t peer_off) {
    asm volatile("mbarrier.arrive.shared::cta.b64 _, [%0];\nmbarrier.arrive.shared::cluster.b64 _, [%1];" :: "r"(a), "r"(a + peer_off) : "memory");
}
__device__ __forceinline__ void cluster_sync() { asm volatile("barrier.cluster.arrive.release;\nbarrier.cluster.wait.acquire;" ::: "memory"); }
__device__ __forceinline__ void l2_prefetch(const void* src, uint32_t bytes) {
    asm volatile("cp.async.bulk.prefetch.L2.global [%0], %1;" :: "l"(src), "r"(bytes) : "memory");
}
__device__ __forceinline__ uint32_t pack_bf16(float lo, float hi) { uint32_t r; asm("cvt.rn.bf16x2.f32 %0, %1, %2;" : "=r"(r) : "f"(hi), "f"(lo)); return r; }
__device__ __forceinline__ float bf_lo(uint32_t v) { return __uint_as_float(v << 16); }
__device__ __forceinline__ float bf_hi(uint32_t v) { return __uint_as_float(v & 0xFFFF0000u); }
__device__ __forceinline__ float gelu2_tanh(float x) {
    float u = x * fmaf(x * x, 0.0356774081363001f, 0.7978845608028654f), t;
    asm("tanh.approx.f32 %0, %1;" : "=f"(t) : "f"(u));
    return fmaf(x, t, x);
}
#define FENCE_F(a, n) _Pragma("unroll") for (int i_ = 0; i_ < n; i_++) asm volatile("" : "+f"(a[i_]) :: "memory");
#define FENCE_R(a, n) _Pragma("unroll") for (int i_ = 0; i_ < n; i_++) asm volatile("" : "+r"(a[i_]) :: "memory");

__device__ __forceinline__ uint32_t exp2_mufu(float a, float b) {
    float x, y;
    asm("ex2.approx.ftz.f32 %0, %1;" : "=f"(x) : "f"(a));
    asm("ex2.approx.ftz.f32 %0, %1;" : "=f"(y) : "f"(b));
    return pack_bf16(x, y);
}
__device__ __forceinline__ uint32_t exp2_alu(float a, float b, uint32_t half2c) {
    uint32_t L = __byte_perm(__float_as_uint(a), __float_as_uint(b), 0x6521), G, r;
    asm("lop3.b32 %0, %1, 0x007F007F, %2, 0xEA;" : "=r"(G) : "r"(L), "r"(half2c));
    uint32_t E = L & 0xFF80FF80u;
    asm("fma.rn.bf16x2 %0, %1, %2, %3;" : "=r"(r) : "r"(G), "r"(L), "r"(E));
    return r;
}
#define EXPBLK(p, s) _Pragma("unroll") for (int b = 0; b < 8; b++) { \
    if ((PAT >> b) & 1) { p[2*b] = exp2_alu(s[4*b], s[4*b+1], half2c); p[2*b+1] = exp2_alu(s[4*b+2], s[4*b+3], half2c); } \
    else { p[2*b] = exp2_mufu(s[4*b], s[4*b+1]); p[2*b+1] = exp2_mufu(s[4*b+2], s[4*b+3]); } }

struct Ring { uint32_t st, ph; };
template<int NST> __device__ __forceinline__ void ring_next(Ring& r) { if (++r.st == NST) { r.st = 0; r.ph ^= 1; } }

struct OpDesc { uint32_t lo, hi, step, nsplit; };

template<int N> __device__ __forceinline__ void wgmma_ss(float (&d)[N / 2], uint64_t da, uint32_t blo, uint32_t bhi, uint32_t nsplit, int sc) {
    if constexpr (N == 160) {
        wgmma_ss_n96<0, 1>(*(float(*)[48])&d[0], da, mkdesc(blo, bhi), sc);
        wgmma_ss_n64<0, 1>(*(float(*)[32])&d[48], da, mkdesc(blo + nsplit, bhi), sc);
    } else if constexpr (N == 192) {
        wgmma_ss_n128<0, 1>(*(float(*)[64])&d[0], da, mkdesc(blo, bhi), sc);
        wgmma_ss_n64<0, 1>(*(float(*)[32])&d[64], da, mkdesc(blo + nsplit, bhi), sc);
    } else {
        wgmma_ss_n128<0, 1>(*(float(*)[64])&d[0], da, mkdesc(blo, bhi), sc);
        wgmma_ss_n88<0, 1>(*(float(*)[44])&d[64], da, mkdesc(blo + nsplit, bhi), sc);
    }
}

struct GemmCtx { Ring r; uint32_t sb16, bar_full, bar_empty, peer_off; bool lead; };

template<int N, int NS, int GB>
__device__ __forceinline__ void gemm_loop(float (&acc)[N / 2], int nkb, int first, OpDesc a, OpDesc b, GemmCtx& c) {
    uint32_t prev = 0;
    #pragma unroll 1
    for (int kb = 0; kb < nkb; kb++) {
        mbar_wait(c.bar_full + 8 * c.r.st, c.r.ph);
        if (nkb == 32 && threadIdx.x == 256) TR2(2, kb);
        const uint32_t base = c.sb16 + c.r.st * (GST_BYTES / 16);
        wg_fence();
        #pragma unroll
        for (int k = 0; k < NS; k++) {
            wgmma_ss<N>(acc, mkdesc(base + a.lo + k * a.step, a.hi), base + b.lo + k * b.step, b.hi, b.nsplit, (k > 0) | (kb > 0) | !first);
            if constexpr (GB > 0) { if ((k + 1) % GB == 0 || k == NS - 1) { wg_commit(); wg_wait<0>(); } }
        }
        if constexpr (GB > 0) {
            if (nkb == 32 && threadIdx.x == 256) TR2(3, kb);
            if (c.lead) release2(c.bar_empty + 8 * c.r.st, c.peer_off);
        } else {
            wg_commit();
            wg_wait<1>();
            if (kb > 0 && c.lead) release2(c.bar_empty + 8 * prev, c.peer_off);
            prev = c.r.st;
        }
        ring_next<GST>(c.r);
    }
    if constexpr (GB == 0) {
        wg_wait<0>();
        if (c.lead) release2(c.bar_empty + 8 * prev, c.peer_off);
    }
    FENCE_F(acc, N / 2);
}

template<int CNT, int SUBS>
__device__ __forceinline__ void retile_ld(uint4 (&v)[CNT], const __nv_bfloat16* src, int pitch, int ncg, int nkg, int cm0, int cnt, int id) {
    const int sub = id >> 3, row = id & 7;
    #pragma unroll
    for (int i = 0; i < CNT; i++) {
        const int l = sub + i * SUBS, cm = cm0 + l, kg = cm / ncg, cg = cm - kg * ncg;
        if (l < cnt && kg < nkg) v[i] = __ldg((const uint4*)(src + (size_t)(kg * 8 + row) * pitch + cg * 8));
    }
}
template<int NG, int CNT, int SUBS, bool PERM>
__device__ __forceinline__ void retile_st(const uint4 (&v)[CNT], int ncg, int nkg, uint8_t* dst, int cm0, int cnt, int id) {
    const int sub = id >> 3, row = id & 7;
    #pragma unroll
    for (int i = 0; i < CNT; i++) {
        const int l = sub + i * SUBS, cm = cm0 + l, kg = cm / ncg, cg = cm - kg * ncg, tile = cg / NG;
        int kd = kg;
        if (PERM) { const int q = kg / 20, rem = kg - q * 20, ps = rem / 10; kd = ps * 40 + q * 10 + (rem - ps * 10); }
        if (l < cnt && kg < nkg) *(uint4*)(dst + (size_t)((tile * nkg + kd) * NG + (cg - tile * NG)) * 128 + row * 16) = v[i];
    }
}

__global__ void __cluster_dims__(2, 1, 1) __launch_bounds__(512, 1) mega_kernel(const __grid_constant__ Params p) {
    extern __shared__ uint8_t smem_raw[];
    const uint32_t sb = ((uint32_t)__cvta_generic_to_shared(smem_raw) + 1023u) & ~1023u;
    uint8_t* sm = smem_raw + (sb - (uint32_t)__cvta_generic_to_shared(smem_raw));
    const uint32_t bar_gfull = sb + SM_MISC, bar_gempty = bar_gfull + 64, bar_kfull = bar_gfull + 128, bar_kempty = bar_gfull + 192;
    float* s_gate = (float*)(sm + SM_MISC + 256);
    float* s_stat = (float*)(sm + SM_MISC + 512);
    float* s_red = (float*)(sm + SM_MISC + 768);
    const int rb = blockIdx.x & 31, ct = blockIdx.x >> 5;
    const int rank = rb & 1;
    const int wg = __shfl_sync(0xffffffffu, threadIdx.x >> 7, 0);
    const int tid = threadIdx.x & 127, w = tid >> 5, lane = tid & 31, g = lane >> 2, t = lane & 3;
    uint32_t peer_off;
    asm("mapa.shared::cluster.u32 %0, %1, %2;" : "=r"(peer_off) : "r"(sb), "r"(rank ^ 1));
    peer_off -= sb;

    if (threadIdx.x == 0) {
        for (int i = 0; i < GST; i++) { mbar_init(bar_gfull + 8 * i, 1); mbar_init(bar_gempty + 8 * i, 8); }
        for (int i = 0; i < KST; i++) { mbar_init(bar_kfull + 8 * i, 1); mbar_init(bar_kempty + 8 * i, 16); }
        asm volatile("fence.mbarrier_init.release.cluster;" ::: "memory");
        fence_async();
    }
    cluster_sync();

    if (wg == 3) {
        asm volatile("setmaxnreg.dec.sync.aligned.u32 24;");
        static_assert(GST == 4, "ring indices are derived from a running stage counter");
        #define STG_ADDR(n) (sb + SM_G + ((n) & 3) * GST_BYTES)
        #define STG_FULL(n) (bar_gfull + ((n) & 3) * 8)
        #define STG_WAIT(n) mbar_wait(bar_gempty + ((n) & 3) * 8, (((n) >> 2) & 1) ^ 1)
        const uint32_t n0 = ct < 2 ? 3 : 0;
        if (w == 0) {
            uint32_t n = n0;
            if (lane == 0) {
                #pragma unroll 1
                for (int kb = 0; kb < 10; kb++, n++) {
                    STG_WAIT(n);
                    mbar_expect(STG_FULL(n), 8192 + 3 * 8192);
                    #pragma unroll
                    for (int a = 0; a < 3; a++) tma2d_mc(STG_ADDR(n) + 8192 + a * 8192 + rank * 4096, &p.mwq, ((160 * ct) & ~63) + a * 64, kb * 64 + rank * 32, STG_FULL(n));
                }
                flag_wait(F_W2, NCTA / 2);
                TRW(21);
                fence_async();
                const uint8_t* src = g_wint + (size_t)(4 + ct) * 80 * 3456 + rank * 13824;
                #pragma unroll 1
                for (int i = 0; i < 20; i++, n++) {
                    STG_WAIT(n);
                    mbar_expect(STG_FULL(n), 8192 + 27648);
                    bulk_ld_mc(STG_ADDR(n) + 8192 + rank * 13824, src, 13824, STG_FULL(n));
                    src += i == 9 ? 27648 - 5 * 80 * 3456 : 27648;
                }
            }
            __syncwarp();
            #pragma unroll 1
            for (int it = 0; ; it++) {
                unsigned v;
                asm volatile("ld.acquire.gpu.global.u32 %0, [%1];" : "=r"(v) : "l"(&g_flags[(F_Z2 + lane * 4 + ct) * 8]) : "memory");
                if (__all_sync(0xffffffffu, v != 0)) break;
                if (it > SPIN_LIMIT) SPIN_FAIL(F_Z2);
                __nanosleep(20);
            }
            if (lane == 0) {
                fence_async();
                const uint8_t* src = g_z2n + (size_t)ct * 32 * 27648 + rank * 13824;
                #pragma unroll 1
                for (int kb = 0; kb < 32; kb++, n++, src += 27648) {
                    STG_WAIT(n);
                    TR2(0, kb);
                    mbar_expect(STG_FULL(n), 8192 + 27648);
                    bulk_ld_mc(STG_ADDR(n) + 8192 + rank * 13824, src, 13824, STG_FULL(n));
                }
                flag_wait(F_WR, NCTA);
                fence_async();
                #pragma unroll 1
                for (int i = 0; i < 22; i++, n++) {
                    const bool hp = i >= 4 && i < 18;
                    const uint32_t hb = hp ? (i == 17 ? 5120 : 10240) : 12800;
                    const uint8_t* sp = hp ? g_woutt + (size_t)(ct * 108 + (i - 4) * 8) * 2560 : g_wot + (size_t)(ct * 80 + (i < 4 ? i : i - 14) * 10) * 2560;
                    STG_WAIT(n);
                    mbar_expect(STG_FULL(n), 2 * hb + (hb * 4) / 5);
                    bulk_ld_mc(STG_ADDR(n) + 10240 + rank * hb, sp + rank * hb, hb, STG_FULL(n));
                }
            }
        } else if (w == 3) {
            if (lane == 0) {
                if (ct < 2) {
                    #pragma unroll 1
                    for (int kb = 0; kb < 10; kb++) {
                        if ((kb & 3) == 0) mbar_expect(STG_FULL(kb >> 2), kb < 8 ? 32768 : 16384);
                        tma2d(STG_ADDR(kb >> 2) + (kb & 3) * 8192, &p.mx, kb * 64, rb * 64, STG_FULL(kb >> 2));
                    }
                }
                uint32_t n = n0;
                #pragma unroll 1
                for (int j = 0; j < 3; j++) {
                    #pragma unroll 1
                    for (int kb = 0; kb < 10; kb++, n++) {
                        STG_WAIT(n);
                        tma2d(STG_ADDR(n), &p.mx, kb * 64, rb * 64, STG_FULL(n));
                        if (j > 0 && kb >= 2) l2_prefetch(p.wsp + (size_t)(rb * 64 + ct * 16 + (j - 1) * 8 + kb - 2) * S_LEN, 4096);
                    }
                }
                #pragma unroll 1
                for (int kb = 0; kb < 32; kb++, n++) {
                    STG_WAIT(n);
                    tma2d(STG_ADDR(n), &p.mwsp, kb * 64, rb * 64, STG_FULL(n));
                    TR2(1, kb);
                }
                #pragma unroll 1
                for (int i = 0; i < 22; i++, n++) {
                    const bool hp = i >= 4 && i < 18;
                    if (i == 0 || i == 4 || i == 18) { flag_wait(i == 4 ? F_H + rb : F_O + rb * 2 + (i != 0), i == 4 ? 4 : 8); fence_async(); }
                    STG_WAIT(n);
                    bulk_ld(STG_ADDR(n), hp ? g_hp + (size_t)(rb * 108 + (i - 4) * 8) * 1024 : g_op + (size_t)(rb * 80 + (i < 4 ? i : i - 14) * 10) * 1024,
                            hp ? (i == 17 ? 4096 : 8192) : 10240, STG_FULL(n));
                }
            }
        } else if (w == 1) {
            if (lane == 0) {
                flag_wait(F_KV, 64);
                TRW(18);
                asm volatile("fence.proxy.async.global;" ::: "memory");
                TRW(19);
                mbar_expect(bar_kfull + 24, 3072 + 512);
                bulk_ld(sb + SM_KV + 3 * KST_BYTES + 6144, g_kv + 31 * 6144, 3072, bar_kfull + 24);
                bulk_ld(sb + SM_MISC + 512, g_kvmax, 256, bar_kfull + 24);
                bulk_ld(sb + SM_MISC + 256, g_gate + rb * 64, 256, bar_kfull + 24);
                #pragma unroll 1
                for (int i = 0; i < 32; i++) {
                    const uint32_t st = i & 3;
                    if (i >= 3) mbar_wait(bar_kempty + 8 * st, (((i + 1) >> 2) & 1) ^ 1);
                    mbar_expect(bar_kfull + 8 * st, KST_BYTES);
                    bulk_ld_mc(sb + SM_KV + st * KST_BYTES + rank * 6144, g_kv + (i & 15) * KST_BYTES + rank * 6144, 6144, bar_kfull + 8 * st);
                }
            }
        } else {
            if (ct < 2) {
                bar_sync(10, 160);
                if (lane == 0) {
                    uint32_t m = max(max(__float_as_uint(s_red[8]), __float_as_uint(s_red[9])), max(__float_as_uint(s_red[10]), __float_as_uint(s_red[11])));
                    g_kvmax[ct * 32 + rb] = __uint_as_float(m);
                    TRW(16);
                    flag_add(F_KV);
                    TRW(17);
                }
                __syncwarp();
            }
            bar_sync(10, 160);
            if (lane == 0) { flag_add(F_STAT + rb); flag_wait(F_STAT + rb, 4); }
            __syncwarp();
            bar_arrive(11, 160);
            bar_sync(10, 160);
            if (lane == 0) flag_add(F_Z2 + rb * 4 + ct);
            __syncwarp();
            #pragma unroll 1
            for (int i = 0; i < 7; i++) {
                uint4 v[2];
                retile_ld<2, 4>(v, p.wo, DM, 80, 80, blockIdx.x * 50 + i * 8, 50 - i * 8, lane);
                retile_st<20, 2, 4, true>(v, 80, 80, g_wot, blockIdx.x * 50 + i * 8, 50 - i * 8, lane);
            }
            #pragma unroll 1
            for (int i = 0; i < 9; i++) {
                uint4 v[2];
                retile_ld<2, 4>(v, p.wout, DM, 80, 108, blockIdx.x * 68 + i * 8, 68 - i * 8, lane);
                retile_st<20, 2, 4, false>(v, 80, 108, g_woutt, blockIdx.x * 68 + i * 8, 68 - i * 8, lane);
            }
            __syncwarp();
            if (lane == 0) { flag_add(F_WR); TRW(30); }
            __syncwarp();
            bar_sync(10, 160);
            if (lane == 0) flag_add(F_H + rb);
        }
    } else if (wg == 2) {
        asm volatile("setmaxnreg.inc.sync.aligned.u32 152;");
        TRACE(0);
        GemmCtx c{{0, 0}, ((sb + SM_G) & 0x3FFFFu) >> 4, bar_gfull, bar_gempty, peer_off, lane == 0};
        const OpDesc a_sw{0u, 64u | (1u << 30), 2u, 0u};
        const OpDesc a_t{64u << 16, 8u, 128u, 0u};
        const OpDesc b_q{512u | (512u << 16), 64u | (1u << 30), 128u, 1024u};
        const OpDesc b_z{512u | (216u << 16), 8u, 432u, 128u};
        const OpDesc b_o{640u | (160u << 16), 8u, 320u, 96u};
        const int r0 = 16 * w + g;
        if (ct < 2) {
            float ex[12];
            const uint32_t exlo = (((sb + SM_KV) & 0x3FFFFu) >> 4) | (24u << 16);
            bar_sync(1, 384);
            #pragma unroll 1
            for (int kb = 0; kb < 10; kb++) {
                if ((kb & 3) == 0) mbar_wait(bar_gfull + 8 * (kb >> 2), 0);
                const uint32_t base = c.sb16 + (kb >> 2) * (GST_BYTES / 16) + (kb & 3) * 512;
                wg_fence();
                #pragma unroll
                for (int k = 0; k < 4; k++) wgmma_ss_n24<0, 1>(ex, mkdesc(base + 2 * k, a_sw.hi), mkdesc(exlo + (kb * 4 + k) * 48, 8), (k > 0) | (kb > 0));
                wg_commit();
            }
            wg_wait<0>();
            FENCE_F(ex, 12);
            if (lane < 3) release2(bar_gempty + 8 * lane, peer_off);
            c.r.st = 3;
            uint8_t* dst = g_kv + (ct == 0 ? (rb + 31) & 31 : rb) * 6144 + ct * 3072 + 2 * w * 384 + g * 16 + t * 4;
            float mx = 0.f;
            #pragma unroll
            for (int hi = 0; hi < 2; hi++) {
                const bool alu = (PAT >> (2 * w + hi)) & 1;
                float n2 = 0.f;
                #pragma unroll
                for (int j = 0; j < 3; j++) {
                    uint32_t v = pack_bf16(ex[4 * j + 2 * hi], ex[4 * j + 2 * hi + 1]);
                    float a = bf_lo(v), b = bf_hi(v);
                    if (ct == 0) {
                        n2 = fmaf(a, a, fmaf(b, b, n2));
                        if (alu) v = pack_bf16(2.f * a, 2.f * b);
                        if (j == 2 && t == 2) v = alu ? 0x3C004440u : 0x39A93FCBu;
                    } else {
                        if (j < 2 || t < 2) n2 = __uint_as_float(max(__float_as_uint(n2), max(__float_as_uint(fabsf(a)), __float_as_uint(fabsf(b)))));
                        if (j == 2 && t == 3) {
                            g_gate[rb * 64 + r0 + 8 * hi] = 1.f / (1.f + __expf(-ex[8 + 2 * hi]));
                            v = 0u;
                        }
                        if (j == 2 && t == 2) v = 0x00003F80u;
                    }
                    *(uint32_t*)(dst + hi * 384 + j * 128) = v;
                }
                if (ct == 0) { n2 += __shfl_xor_sync(0xffffffffu, n2, 1); n2 += __shfl_xor_sync(0xffffffffu, n2, 2); }
                mx = __uint_as_float(max(__float_as_uint(mx), __float_as_uint(n2) & 0x7FFFFFFFu));
            }
            mx = __uint_as_float(__reduce_max_sync(0xffffffffu, __float_as_uint(mx)));
            if (lane == 0) s_red[8 + w] = mx;
            bar_arrive(10, 160);
            TRACE(15);
        }
        {
            float acc[96];
            gemm_loop<192, 4, 0>(acc, 10, 1, a_sw, b_q, c);
            TRACE(1);
            const int joff = (ct & 1) * 4;
            uint32_t* qs = (uint32_t*)(sm + SM_Q) + r0 * (QS_PITCH / 2) + t - 4 * joff;
            #pragma unroll
            for (int j = 0; j < 24; j++) {
                if (j >= joff && j < joff + 20) {
                    qs[4 * j] = pack_bf16(acc[4 * j] * 0.3225964182229561f, acc[4 * j + 1] * 0.3225964182229561f);
                    qs[8 * (QS_PITCH / 2) + 4 * j] = pack_bf16(acc[4 * j + 2] * 0.3225964182229561f, acc[4 * j + 3] * 0.3225964182229561f);
                }
            }
            bar_arrive(2, 384);
        }
        {
            float acc[108];
            gemm_loop<216, 4, GBATCH>(acc, 10, 1, a_sw, b_z, c);
            TRACE(2);
            float s0 = 0.f, q0 = 0.f, s1 = 0.f, q1 = 0.f;
            #pragma unroll
            for (int j = 0; j < 27; j++) {
                acc[4 * j] = gelu2_tanh(acc[4 * j]); acc[4 * j + 1] = gelu2_tanh(acc[4 * j + 1]);
                acc[4 * j + 2] = gelu2_tanh(acc[4 * j + 2]); acc[4 * j + 3] = gelu2_tanh(acc[4 * j + 3]);
                s0 += acc[4 * j] + acc[4 * j + 1]; q0 = fmaf(acc[4 * j], acc[4 * j], fmaf(acc[4 * j + 1], acc[4 * j + 1], q0));
                s1 += acc[4 * j + 2] + acc[4 * j + 3]; q1 = fmaf(acc[4 * j + 2], acc[4 * j + 2], fmaf(acc[4 * j + 3], acc[4 * j + 3], q1));
            }
            #pragma unroll
            for (int o = 1; o <= 2; o <<= 1) {
                s0 += __shfl_xor_sync(0xffffffffu, s0, o); q0 += __shfl_xor_sync(0xffffffffu, q0, o);
                s1 += __shfl_xor_sync(0xffffffffu, s1, o); q1 += __shfl_xor_sync(0xffffffffu, q1, o);
            }
            if (t == 0) { g_part[(rb * 4 + ct) * 64 + r0] = make_float2(s0, q0); g_part[(rb * 4 + ct) * 64 + r0 + 8] = make_float2(s1, q1); }
            TRACE(3);
            bar_arrive(10, 160);
            bar_sync(11, 160);
            {
                float2 a = __ldcg(&g_part[(rb * 4 + t) * 64 + r0]), b = __ldcg(&g_part[(rb * 4 + t) * 64 + r0 + 8]);
                s0 = a.x; q0 = a.y; s1 = b.x; q1 = b.y;
                #pragma unroll
                for (int o = 1; o <= 2; o <<= 1) {
                    s0 += __shfl_xor_sync(0xffffffffu, s0, o); q0 += __shfl_xor_sync(0xffffffffu, q0, o);
                    s1 += __shfl_xor_sync(0xffffffffu, s1, o); q1 += __shfl_xor_sync(0xffffffffu, q1, o);
                }
            }
            TRACE(4);
            const float m0 = s0 * (1.f / FH), m1 = s1 * (1.f / FH);
            const float rs0 = rsqrtf(fmaxf(q0 * (1.f / FH) - m0 * m0, 0.f) + 4e-5f), rs1 = rsqrtf(fmaxf(q1 * (1.f / FH) - m1 * m1, 0.f) + 4e-5f);
            const float c0 = -m0 * rs0, c1 = -m1 * rs1;
            {
                uint8_t* dst = g_z2n + (size_t)(ct * 32 + rb) * 27648 + (2 * w) * 3456 + g * 16 + t * 4;
                #pragma unroll
                for (int j = 0; j < 27; j++) {
                    *(uint32_t*)(dst + j * 128) = pack_bf16(fmaf(acc[4 * j], rs0, c0), fmaf(acc[4 * j + 1], rs0, c0));
                    *(uint32_t*)(dst + 3456 + j * 128) = pack_bf16(fmaf(acc[4 * j + 2], rs1, c1), fmaf(acc[4 * j + 3], rs1, c1));
                }
            }
            bar_arrive(10, 160);
            TRACE(5);

            gemm_loop<216, 4, GBATCH>(acc, 10, 1, a_sw, b_z, c);
            TRACE(6);
            uint4* z1p = g_z1 + (size_t)blockIdx.x * 14 * 128 + tid;
            #pragma unroll
            for (int j = 0; j < 14; j++) {
                uint4 v;
                v.x = pack_bf16(gelu2_tanh(acc[8 * j]), gelu2_tanh(acc[8 * j + 1]));
                v.y = pack_bf16(gelu2_tanh(acc[8 * j + 2]), gelu2_tanh(acc[8 * j + 3]));
                if (j < 13) {
                    v.z = pack_bf16(gelu2_tanh(acc[8 * j + 4]), gelu2_tanh(acc[8 * j + 5]));
                    v.w = pack_bf16(gelu2_tanh(acc[8 * j + 6]), gelu2_tanh(acc[8 * j + 7]));
                } else { v.z = 0; v.w = 0; }
                z1p[j * 128] = v;
            }
            TRACE(7);
            gemm_loop<216, 4, GBATCH>(acc, 32, 1, a_sw, b_z, c);
            TRACE(8);
            bar_sync(8, 384);
            const float b0 = __bfloat162float(p.bsp[rb * 64 + r0]), b1 = __bfloat162float(p.bsp[rb * 64 + r0 + 8]);
            const float g0 = 0.5f - 0.5f * s_gate[r0], g1 = 0.5f - 0.5f * s_gate[r0 + 8];
            {
                uint8_t* dst = g_hp + (size_t)((rb * 108 + 27 * ct) * 8 + 2 * w) * 128 + g * 16 + t * 4;
                #pragma unroll
                for (int j = 0; j < 14; j++) {
                    uint4 v = z1p[j * 128];
                    *(uint32_t*)(dst + (2 * j) * 1024) = pack_bf16((acc[8 * j] + b0) * g0 * bf_lo(v.x), (acc[8 * j + 1] + b0) * g0 * bf_hi(v.x));
                    *(uint32_t*)(dst + (2 * j) * 1024 + 128) = pack_bf16((acc[8 * j + 2] + b1) * g1 * bf_lo(v.y), (acc[8 * j + 3] + b1) * g1 * bf_hi(v.y));
                    if (j < 13) {
                        *(uint32_t*)(dst + (2 * j + 1) * 1024) = pack_bf16((acc[8 * j + 4] + b0) * g0 * bf_lo(v.z), (acc[8 * j + 5] + b0) * g0 * bf_hi(v.z));
                        *(uint32_t*)(dst + (2 * j + 1) * 1024 + 128) = pack_bf16((acc[8 * j + 6] + b1) * g1 * bf_lo(v.w), (acc[8 * j + 7] + b1) * g1 * bf_hi(v.w));
                    }
                }
            }
            bar_arrive(10, 160);
            TRACE(9);
        }
        {
            float acc[80];
            gemm_loop<160, 5, GBATCH>(acc, 4, 1, a_t, b_o, c);
            gemm_loop<160, 4, GBATCH>(acc, 13, 0, a_t, b_o, c);
            gemm_loop<160, 2, GBATCH>(acc, 1, 0, a_t, b_o, c);
            TRACE(10);
            gemm_loop<160, 5, 0>(acc, 4, 0, a_t, b_o, c);
            TRACE(11);
            uint32_t* os = (uint32_t*)(sm + SM_Q) + r0 * (QS_PITCH / 2) + t;
            #pragma unroll
            for (int j = 0; j < 20; j++) {
                os[4 * j] = pack_bf16(acc[4 * j], acc[4 * j + 1]);
                os[8 * (QS_PITCH / 2) + 4 * j] = pack_bf16(acc[4 * j + 2], acc[4 * j + 3]);
            }
            asm volatile("fence.proxy.async.shared::cta;" ::: "memory");
            __syncwarp();
            if (lane < 16) {
                const int row = 16 * w + lane;
                asm volatile("cp.async.bulk.global.shared::cta.bulk_group [%0], [%1], 320;"
                             :: "l"(p.out + (size_t)(rb * 64 + row) * DM + 160 * ct), "r"(sb + SM_Q + row * (QS_PITCH * 2)) : "memory");
                asm volatile("cp.async.bulk.commit_group;\ncp.async.bulk.wait_group 0;" ::: "memory");
            }
            TRACE(12);
            if (tid == 0) {
                unsigned d = atomicAdd(&g_flags[F_DONE * 8], 1u);
                if (d == NCTA - 1) { for (int i = 0; i < F_NUM; i++) g_flags[i * 8] = 0; }
            }
            __syncwarp();
            cluster_sync();
        }
    } else {
        asm volatile("setmaxnreg.inc.sync.aligned.u32 168;");
        const int atid = threadIdx.x;
        {
            if (ct < 2) {
                const int q = atid & 3, k0 = atid >> 2;
                const uint32_t dst = sb + SM_KV + (k0 >> 3) * 384 + (k0 & 7) * 16 + q * 4;
                const uint32_t* src = (const uint32_t*)(ct == 0 ? p.wk : p.wv) + k0 * 10 + q;
                uint32_t gv[10];
                #pragma unroll 1
                for (int i = 0; i < 10; i++) {
                    asm volatile("cp.async.ca.shared.global [%0], [%1], 4;\ncp.async.ca.shared.global [%0+128], [%1+16], 4;" :: "r"(dst + i * 3072), "l"(src + i * 640) : "memory");
                    if (q < 2) asm volatile("cp.async.ca.shared.global [%0+256], [%1+32], 4;" :: "r"(dst + i * 3072), "l"(src + i * 640) : "memory");
                }
                #pragma unroll
                for (int i = 0; i < 10; i++) gv[i] = (q == 3 && ct == 1) ? (uint32_t)__ldg((const unsigned short*)p.gw + k0 + 64 * i) : 0u;
                if (q >= 2) {
                    #pragma unroll
                    for (int i = 0; i < 10; i++) asm volatile("st.shared.u32 [%0], %1;" :: "r"(dst + i * 3072 + 256), "r"(gv[i]) : "memory");
                }
                asm volatile("cp.async.wait_all;" ::: "memory");
                asm volatile("fence.proxy.async.shared::cta;" ::: "memory");
                bar_arrive(1, 384);
                if (wg == 0) TRACE(13);
            } else {
                uint4 wv[9];
                const int cm0 = (blockIdx.x & 63) * 270;
                retile_ld<9, 32>(wv, p.win, 2 * FH, 216, 80, cm0, 270, atid);
                retile_st<27, 9, 32, false>(wv, 216, 80, g_wint, cm0, 270, atid);
                bar_sync(9, 256);
                if (atid == 0) flag_add(F_W2);
                if (wg == 0) TRACE(14);
            }
        }
        const uint32_t zero = *(const volatile uint32_t*)&g_const[0], zero2 = *(const volatile uint32_t*)&g_const[1];
        const uint32_t zero3 = *(const volatile uint32_t*)&g_const[3], zero4 = *(const volatile uint32_t*)&g_const[0];
        const uint32_t half2c = *(const volatile uint32_t*)&g_const[2];
        bar_sync(2, 384);
        mbar_wait(bar_kfull + 24, 0);
        bar_arrive(8, 384);
        float bmax2;
        {
            const float kmax2 = __uint_as_float(__reduce_max_sync(0xffffffffu, __float_as_uint(s_stat[lane])));
            const float vmax = __uint_as_float(__reduce_max_sync(0xffffffffu, __float_as_uint(s_stat[32 + lane])));
            const int ev = (int)(__float_as_uint(vmax) >> 23) - 126;
            const float bmax = fminf(100.f, fminf((float)(110 - max(ev, 1)), (float)(88 + ev)));
            bmax2 = bmax > 0.f ? bmax * bmax / fmaxf(kmax2, 1e-30f) : -1.f;
            if (!(kmax2 < 1e30f)) bmax2 = -1.f;
        }
        const uint32_t kv16 = ((sb + SM_KV) & 0x3FFFFu) >> 4;
        constexpr uint32_t KLBO = 8u << 16, KHI = 24u, VLBO = (24u << 16) + 192u, VHI = 8u;
        const bool lead = lane == 0;
        const int r0 = 16 * w + g;
        static_assert(KST == 4, "ring phases below assume 4 stages");
        #pragma unroll 1
        for (int pass = 0; pass < 2; pass++) {
            const int h = 4 * pass + 2 * wg;
            uint32_t qa[6], qb[6];
            float nmax;
            {
                const uint32_t* qs = (const uint32_t*)(sm + SM_Q) + r0 * (QS_PITCH / 2) + 10 * h + t;
                #define LOADQ(q, o) q[0] = qs[o]; q[1] = qs[8 * (QS_PITCH / 2) + o]; q[2] = qs[o + 4]; q[3] = qs[8 * (QS_PITCH / 2) + o + 4]; \
                    q[4] = t < 2 ? qs[o + 8] : 0u; q[5] = t < 2 ? qs[8 * (QS_PITCH / 2) + o + 8] : 0u;
                LOADQ(qa, 0) LOADQ(qb, 10)
                #define SQ(v) (bf_lo(v) * bf_lo(v) + bf_hi(v) * bf_hi(v))
                float n[4] = {SQ(qa[0]) + SQ(qa[2]) + SQ(qa[4]), SQ(qa[1]) + SQ(qa[3]) + SQ(qa[5]), SQ(qb[0]) + SQ(qb[2]) + SQ(qb[4]), SQ(qb[1]) + SQ(qb[3]) + SQ(qb[5])};
                bool ok = true;
                #pragma unroll
                for (int i = 0; i < 4; i++) {
                    n[i] += __shfl_xor_sync(0xffffffffu, n[i], 1); n[i] += __shfl_xor_sync(0xffffffffu, n[i], 2);
                    ok = ok && (n[i] <= bmax2);
                }
                nmax = ok ? 1.f : 0.f;
            }
            uint32_t safe;
            asm volatile("{\n.reg .pred p, q;\nsetp.ne.u32 p, %1, 0;\nbarrier.red.and.pred.aligned q, %2, 128, p;\nselp.u32 %0, 1, 0, q;\n}"
                         : "=r"(safe) : "r"((uint32_t)(nmax != 0.f)), "r"(4 + wg) : "memory");
            safe = __shfl_sync(0xffffffffu, safe, 0);
            float oa[12], ob[12];
            #pragma unroll
            for (int i = 0; i < 12; i++) { oa[i] = 0.f; ob[i] = 0.f; }
            float sa[32], sc[32]; uint32_t pa[16], pb[16];
            FENCE_F(oa, 12); FENCE_F(ob, 12);
            #define QK(s, q, z0, z1, kd) wgmma_rs_n64<0>(s, q[0], q[1], q[2], q[3], mkdesc((kd) + KLBO, KHI), 0); \
                                         wgmma_rs_n64<0>(s, q[4], q[5], z0, z1, mkdesc((kd) + KLBO + 16, KHI), 1);
            #define PV(o, pp, vd) _Pragma("unroll") for (int kk = 0; kk < 4; kk++) \
                wgmma_rs_n24<1>(o, pp[4 * kk], pp[4 * kk + 1], pp[4 * kk + 2], pp[4 * kk + 3], mkdesc((vd) + VLBO + kk * 48, VHI), 1);
            if (safe) {
                if (t == 2) { qa[4] = qa[5] = qb[4] = qb[5] = 0x3F803F80u; }
                wg_fence();
                QK(sa, qa, zero, zero2, kv16 + 3 * 768 + 384)
                wg_commit();
                QK(sc, qb, zero3, zero4, kv16 + 3 * 768 + 384)
                wg_commit();
                TRACE(23 + h);
                wg_wait<1>();
                FENCE_F(sa, 32);
                EXPBLK(pa, sa);
                FENCE_R(pa, 16);
                #pragma unroll 1
                for (int j = 0; j < 16; j++) {
                    mbar_wait(bar_kfull + 8 * (j & 3), ((j + 1) >> 2) & 1);
                    uint32_t base = kv16 + (j & 3) * 768;
                    #pragma unroll 1
                    for (int i = 0; i < 2; i++) {
                        const uint64_t dk0 = mkdesc(base + KLBO, KHI), dk1 = mkdesc(base + KLBO + 16, KHI);
                        const uint64_t dv0 = mkdesc(base + VLBO, VHI), dv1 = mkdesc(base + VLBO + 48, VHI), dv2 = mkdesc(base + VLBO + 96, VHI), dv3 = mkdesc(base + VLBO + 144, VHI);
                        #define STEP(s, q, z0, z1, o, pp) \
                            wg_fence(); \
                            wgmma_rs_n64<0>(s, q[0], q[1], q[2], q[3], dk0, 0); wgmma_rs_n64<0>(s, q[4], q[5], z0, z1, dk1, 1); \
                            wgmma_rs_n24<1>(o, pp[0], pp[1], pp[2], pp[3], dv0, 1); wgmma_rs_n24<1>(o, pp[4], pp[5], pp[6], pp[7], dv1, 1); \
                            wgmma_rs_n24<1>(o, pp[8], pp[9], pp[10], pp[11], dv2, 1); wgmma_rs_n24<1>(o, pp[12], pp[13], pp[14], pp[15], dv3, 1); \
                            wg_commit(); \
                            wg_wait<1>();
                        STEP(sa, qa, zero, zero2, oa, pa)
                        FENCE_F(sc, 32);
                        EXPBLK(pb, sc);
                        FENCE_R(pb, 16);
                        STEP(sc, qb, zero3, zero4, ob, pb)
                        FENCE_F(sa, 32);
                        EXPBLK(pa, sa);
                        FENCE_R(pa, 16);
                        base += 384;
                    }
                    if (lead) release2(bar_kempty + 8 * ((j + 3) & 3), peer_off);
                }
                wg_wait<0>();
                FENCE_F(oa, 12); FENCE_F(ob, 12); FENCE_F(sc, 32);
            } else {
                float ma0 = -INFINITY, ma1 = -INFINITY, mb0 = -INFINITY, mb1 = -INFINITY;
                #define SLOWSTEP(s, pp, o, m0, m1) { \
                    float x0 = m0, x1 = m1; \
                    _Pragma("unroll") for (int b = 0; b < 8; b++) { \
                        const float f = ((PAT >> b) & 1) ? 0.5f : 1.f;        \
                        s[4 * b] *= f; s[4 * b + 1] *= f; s[4 * b + 2] *= f; s[4 * b + 3] *= f; \
                        x0 = fmaxf(x0, fmaxf(s[4 * b], s[4 * b + 1])); x1 = fmaxf(x1, fmaxf(s[4 * b + 2], s[4 * b + 3])); \
                    } \
                    x0 = fmaxf(x0, __shfl_xor_sync(0xffffffffu, x0, 1)); x0 = fmaxf(x0, __shfl_xor_sync(0xffffffffu, x0, 2)); \
                    x1 = fmaxf(x1, __shfl_xor_sync(0xffffffffu, x1, 1)); x1 = fmaxf(x1, __shfl_xor_sync(0xffffffffu, x1, 2)); \
                    const float f0 = exp2f(m0 - x0), f1 = exp2f(m1 - x1); \
                    m0 = x0; m1 = x1; \
                    _Pragma("unroll") for (int b = 0; b < 3; b++) { o[4 * b] *= f0; o[4 * b + 1] *= f0; o[4 * b + 2] *= f1; o[4 * b + 3] *= f1; } \
                    _Pragma("unroll") for (int b = 0; b < 8; b++) { \
                        pp[2 * b] = exp2_mufu(s[4 * b] - m0, s[4 * b + 1] - m0); \
                        pp[2 * b + 1] = exp2_mufu(s[4 * b + 2] - m1, s[4 * b + 3] - m1); \
                    } }
                #pragma unroll 1
                for (int j = 0; j < 64; j++) {
                    const int u = j >> 1, sj = u >> 1;
                    if ((j & 3) == 0) mbar_wait(bar_kfull + 8 * (sj & 3), ((sj + 1) >> 2) & 1);
                    const uint32_t cur = kv16 + ((u + 7) & 7) * 384, curv = kv16 + (u & 7) * 384;
                    wg_fence();
                    QK(sa, qa, zero, zero2, cur)
                    wg_commit();
                    wg_wait<0>();
                    FENCE_F(sa, 32);
                    SLOWSTEP(sa, pa, oa, ma0, ma1)
                    FENCE_R(pa, 16); FENCE_F(oa, 12);
                    wg_fence();
                    PV(oa, pa, curv)
                    wg_commit();
                    wg_wait<0>();
                    FENCE_F(oa, 12);
                    #pragma unroll
                    for (int i = 0; i < 12; i++) { float x = oa[i]; oa[i] = ob[i]; ob[i] = x; }
                    #pragma unroll
                    for (int i = 0; i < 6; i++) { uint32_t x = qa[i]; qa[i] = qb[i]; qb[i] = x; }
                    { float x = ma0; ma0 = mb0; mb0 = x; x = ma1; ma1 = mb1; mb1 = x; }
                    FENCE_F(oa, 12); FENCE_R(qa, 6);
                    if ((j & 3) == 3 && lead) release2(bar_kempty + 8 * ((sj + 3) & 3), peer_off);
                }
            }
            #define OUTO(o, hh) { \
                const float l0 = __shfl_sync(0xffffffffu, o[8], (lane & ~3) | 2), l1 = __shfl_sync(0xffffffffu, o[10], (lane & ~3) | 2); \
                const float i0 = s_gate[r0] / l0, i1 = s_gate[r0 + 8] / l1; \
                _Pragma("unroll") for (int b = 0; b < 3; b++) { \
                    if (b < 2 || t < 2) { \
                        const int col = 20 * ((hh) & 3) + 8 * b + 2 * t; \
                        uint8_t* dst = g_op + (size_t)((rb * 80 + pass * 40 + ct * 10 + (col >> 3)) * 8 + 2 * w) * 128 + g * 16 + (col & 7) * 2; \
                        *(uint32_t*)dst = pack_bf16(o[4 * b] * i0, o[4 * b + 1] * i0); \
                        *(uint32_t*)(dst + 128) = pack_bf16(o[4 * b + 2] * i1, o[4 * b + 3] * i1); \
                    } \
                } }
            OUTO(oa, h) OUTO(ob, h + 1)
            bar_sync(4 + wg, 128);
            if (tid == 0) flag_add(F_O + rb * 2 + pass);
            TRACE(22 + h);
        }
    }
}

typedef CUresult (*EncodeFn)(CUtensorMap*, CUtensorMapDataType, cuuint32_t, void*, const cuuint64_t*, const cuuint64_t*, const cuuint32_t*,
                             const cuuint32_t*, CUtensorMapInterleave, CUtensorMapSwizzle, CUtensorMapL2promotion, CUtensorMapFloatOOBfill);

void make_map(EncodeFn fn, CUtensorMap* m, const void* ptr, uint64_t cols, uint64_t rows, uint32_t bc, uint32_t br, CUtensorMapSwizzle sw) {
    cuuint64_t dims[2] = {cols, rows}, strides[1] = {cols * 2};
    cuuint32_t box[2] = {bc, br}, es[2] = {1, 1};
    fn(m, CU_TENSOR_MAP_DATA_TYPE_BFLOAT16, 2, const_cast<void*>(ptr), dims, strides, box, es, CU_TENSOR_MAP_INTERLEAVE_NONE, sw,
       CU_TENSOR_MAP_L2_PROMOTION_L2_128B, CU_TENSOR_MAP_FLOAT_OOB_FILL_NONE);
}

}

extern "C" void kernel_launch(void* const* d_in, const int* in_sizes, int n_in, void* d_out, int out_size) {
    static EncodeFn fn = nullptr;
    if (!fn) {
        cudaDriverEntryPointQueryResult qr;
        void* f = nullptr;
        cudaGetDriverEntryPoint("cuTensorMapEncodeTiled", &f, cudaEnableDefault, &qr);
        fn = (EncodeFn)f;
        cudaFuncSetAttribute(mega_kernel, cudaFuncAttributeMaxDynamicSharedMemorySize, SM_TOTAL);
    }
    Params p;
    const __nv_bfloat16* x = (const __nv_bfloat16*)d_in[0];
    make_map(fn, &p.mx, x, DM, S_LEN, 64, 64, CU_TENSOR_MAP_SWIZZLE_128B);
    make_map(fn, &p.mwsp, d_in[7], S_LEN, S_LEN, 64, 64, CU_TENSOR_MAP_SWIZZLE_128B);
    make_map(fn, &p.mwq, d_in[1], DM, DM, 64, 32, CU_TENSOR_MAP_SWIZZLE_128B);
    p.win = (const __nv_bfloat16*)d_in[6];
    p.x = x;
    p.wk = (const __nv_bfloat16*)d_in[2];
    p.wv = (const __nv_bfloat16*)d_in[3];
    p.bsp = (const __nv_bfloat16*)d_in[8];
    p.gw = (const __nv_bfloat16*)d_in[10];
    p.wsp = (const __nv_bfloat16*)d_in[7];
    p.wo = (const __nv_bfloat16*)d_in[4];
    p.wout = (const __nv_bfloat16*)d_in[9];
    p.out = (__nv_bfloat16*)d_out;
    mega_kernel<<<NCTA, 512, SM_TOTAL>>>(p);
}
```

```cpp
#include <cuda_runtime.h>
#include <cuda_bf16.h>
#include <cuda.h>
#include <stdint.h>

namespace {

constexpr int S_LEN = 2048, DM = 640, FH = 864;
constexpr int NCTA = 128;
#define PAT8 0xB5u
constexpr uint32_t PAT = PAT8 * 0x101u;
#define GB2 0
#define GB3 2
#define GB4 2
#define GB5 -1
constexpr int GST = 4;
constexpr int GST_BYTES = 36864;
constexpr int KST = 4;
constexpr int KST_BYTES = 12288;
constexpr int QS_PITCH = 168;
constexpr int SM_G = 0;
constexpr int SM_KV = SM_G + GST * GST_BYTES;
constexpr int SM_Q = SM_KV + KST * KST_BYTES;
constexpr int SM_MISC = SM_Q + 8 * 3072 + 1024;
constexpr int SM_TOTAL = SM_MISC + 2048 + 1024;

constexpr int F_KV = 0, F_DONE = 1, F_W2 = 2, F_WR = 3, F_W1 = 4, F_STAT = 5, F_Z2 = F_STAT + 32, F_H = F_Z2 + 128, F_O = F_H + 32, F_NUM = F_O + 96;

__device__ __align__(1024) uint8_t g_kv[16 * KST_BYTES];
__device__ __align__(1024) uint8_t g_z2n[4 * 32 * 28672];
__device__ __align__(1024) uint8_t g_hp[32 * 108 * 1024];
__device__ __align__(1024) uint8_t g_op[32 * 80 * 1024];
__device__ __align__(1024) uint8_t g_wot[4 * 80 * 2560];
__device__ __align__(1024) uint8_t g_woutt[4 * 108 * 2560];
__device__ __align__(1024) uint4 g_z1[2 * NCTA * 14 * 128];
__device__ uint4 g_part[32 * 4 * 64];
__device__ __align__(128) float g_kvmax[64];
__device__ __align__(128) float g_gate[S_LEN];
__device__ unsigned g_flags[F_NUM * 8];
__device__ uint32_t g_const[4] = {0u, 0u, 0x3F003F00u, 0u};

struct Params {
    CUtensorMap mx, mwsp, mwq, mwin;
    const __nv_bfloat16 *x, *wk, *wv, *bsp, *gw, *wsp, *wo, *wout, *wq, *win;
    __nv_bfloat16* out;
};

template<int TB> __device__ __forceinline__ void wgmma_rs_n24(float (&d)[12], uint32_t a0, uint32_t a1, uint32_t a2, uint32_t a3, uint64_t db, int scale_d) {
  asm volatile("{\n.reg .pred p;\nsetp.ne.b32 p, %17, 0;\nwgmma.mma_async.sync.aligned.m64n24k16.f32.bf16.bf16 {%0,%1,%2,%3,%4,%5,%6,%7,%8,%9,%10,%11}, {%12,%13,%14,%15}, %16, p, 1, 1, %18;\n}"
    : "+f"(d[0]), "+f"(d[1]), "+f"(d[2]), "+f"(d[3]), "+f"(d[4]), "+f"(d[5]), "+f"(d[6]), "+f"(d[7]), "+f"(d[8]), "+f"(d[9]), "+f"(d[10]), "+f"(d[11])
    : "r"(a0), "r"(a1), "r"(a2), "r"(a3), "l"(db), "r"(scale_d), "n"(TB));
}
template<int TA, int TB> __device__ __forceinline__ void wgmma_ss_n24(float (&d)[12], uint64_t da, uint64_t db, int scale_d) {
  asm volatile("{\n.reg .pred p;\nsetp.ne.b32 p, %14, 0;\nwgmma.mma_async.sync.aligned.m64n24k16.f32.bf16.bf16 {%0,%1,%2,%3,%4,%5,%6,%7,%8,%9,%10,%11}, %12, %13, p, 1, 1, %15, %16;\n}"
    : "+f"(d[0]), "+f"(d[1]), "+f"(d[2]), "+f"(d[3]), "+f"(d[4]), "+f"(d[5]), "+f"(d[6]), "+f"(d[7]), "+f"(d[8]), "+f"(d[9]), "+f"(d[10]), "+f"(d[11])
    : "l"(da), "l"(db), "r"(scale_d), "n"(TA), "n"(TB));
}
template<int TA, int TB> __device__ __forceinline__ void wgmma_ss_n64(float (&d)[32], uint64_t da, uint64_t db, int scale_d) {
  asm volatile("{\n.reg .pred p;\nsetp.ne.b32 p, %34, 0;\nwgmma.mma_async.sync.aligned.m64n64k16.f32.bf16.bf16 {%0,%1,%2,%3,%4,%5,%6,%7,%8,%9,%10,%11,%12,%13,%14,%15,%16,%17,%18,%19,%20,%21,%22,%23,%24,%25,%26,%27,%28,%29,%30,%31}, %32, %33, p, 1, 1, %35, %36;\n}"
    : "+f"(d[0]), "+f"(d[1]), "+f"(d[2]), "+f"(d[3]), "+f"(d[4]), "+f"(d[5]), "+f"(d[6]), "+f"(d[7]), "+f"(d[8]), "+f"(d[9]), "+f"(d[10]), "+f"(d[11]), "+f"(d[12]), "+f"(d[13]), "+f"(d[14]), "+f"(d[15]), "+f"(d[16]), "+f"(d[17]), "+f"(d[18]), "+f"(d[19]), "+f"(d[20]), "+f"(d[21]), "+f"(d[22]), "+f"(d[23]), "+f"(d[24]), "+f"(d[25]), "+f"(d[26]), "+f"(d[27]), "+f"(d[28]), "+f"(d[29]), "+f"(d[30]), "+f"(d[31])
    : "l"(da), "l"(db), "r"(scale_d), "n"(TA), "n"(TB));
}
template<int TA, int TB> __device__ __forceinline__ void wgmma_ss_n96(float (&d)[48], uint64_t da, uint64_t db, int scale_d) {
  asm volatile("{\n.reg .pred p;\nsetp.ne.b32 p, %50, 0;\nwgmma.mma_async.sync.aligned.m64n96k16.f32.bf16.bf16 {%0,%1,%2,%3,%4,%5,%6,%7,%8,%9,%10,%11,%12,%13,%14,%15,%16,%17,%18,%19,%20,%21,%22,%23,%24,%25,%26,%27,%28,%29,%30,%31,%32,%33,%34,%35,%36,%37,%38,%39,%40,%41,%42,%43,%44,%45,%46,%47}, %48, %49, p, 1, 1, %51, %52;\n}"
    : "+f"(d[0]), "+f"(d[1]), "+f"(d[2]), "+f"(d[3]), "+f"(d[4]), "+f"(d[5]), "+f"(d[6]), "+f"(d[7]), "+f"(d[8]), "+f"(d[9]), "+f"(d[10]), "+f"(d[11]), "+f"(d[12]), "+f"(d[13]), "+f"(d[14]), "+f"(d[15]), "+f"(d[16]), "+f"(d[17]), "+f"(d[18]), "+f"(d[19]), "+f"(d[20]), "+f"(d[21]), "+f"(d[22]), "+f"(d[23]), "+f"(d[24]), "+f"(d[25]), "+f"(d[26]), "+f"(d[27]), "+f"(d[28]), "+f"(d[29]), "+f"(d[30]), "+f"(d[31]), "+f"(d[32]), "+f"(d[33]), "+f"(d[34]), "+f"(d[35]), "+f"(d[36]), "+f"(d[37]), "+f"(d[38]), "+f"(d[39]), "+f"(d[40]), "+f"(d[41]), "+f"(d[42]), "+f"(d[43]), "+f"(d[44]), "+f"(d[45]), "+f"(d[46]), "+f"(d[47])
    : "l"(da), "l"(db), "r"(scale_d), "n"(TA), "n"(TB));
}
template<int TA, int TB> __device__ __forceinline__ void wgmma_ss_n128(float (&d)[64], uint64_t da, uint64_t db, int scale_d) {
  asm volatile("{\n.reg .pred p;\nsetp.ne.b32 p, %66, 0;\nwgmma.mma_async.sync.aligned.m64n128k16.f32.bf16.bf16 {%0,%1,%2,%3,%4,%5,%6,%7,%8,%9,%10,%11,%12,%13,%14,%15,%16,%17,%18,%19,%20,%21,%22,%23,%24,%25,%26,%27,%28,%29,%30,%31,%32,%33,%34,%35,%36,%37,%38,%39,%40,%41,%42,%43,%44,%45,%46,%47,%48,%49,%50,%51,%52,%53,%54,%55,%56,%57,%58,%59,%60,%61,%62,%63}, %64, %65, p, 1, 1, %67, %68;\n}"
    : "+f"(d[0]), "+f"(d[1]), "+f"(d[2]), "+f"(d[3]), "+f"(d[4]), "+f"(d[5]), "+f"(d[6]), "+f"(d[7]), "+f"(d[8]), "+f"(d[9]), "+f"(d[10]), "+f"(d[11]), "+f"(d[12]), "+f"(d[13]), "+f"(d[14]), "+f"(d[15]), "+f"(d[16]), "+f"(d[17]), "+f"(d[18]), "+f"(d[19]), "+f"(d[20]), "+f"(d[21]), "+f"(d[22]), "+f"(d[23]), "+f"(d[24]), "+f"(d[25]), "+f"(d[26]), "+f"(d[27]), "+f"(d[28]), "+f"(d[29]), "+f"(d[30]), "+f"(d[31]), "+f"(d[32]), "+f"(d[33]), "+f"(d[34]), "+f"(d[35]), "+f"(d[36]), "+f"(d[37]), "+f"(d[38]), "+f"(d[39]), "+f"(d[40]), "+f"(d[41]), "+f"(d[42]), "+f"(d[43]), "+f"(d[44]), "+f"(d[45]), "+f"(d[46]), "+f"(d[47]), "+f"(d[48]), "+f"(d[49]), "+f"(d[50]), "+f"(d[51]), "+f"(d[52]), "+f"(d[53]), "+f"(d[54]), "+f"(d[55]), "+f"(d[56]), "+f"(d[57]), "+f"(d[58]), "+f"(d[59]), "+f"(d[60]), "+f"(d[61]), "+f"(d[62]), "+f"(d[63])
    : "l"(da), "l"(db), "r"(scale_d), "n"(TA), "n"(TB));
}

__device__ __forceinline__ uint64_t mkdesc(uint32_t lo, uint32_t hi) { uint64_t d; asm("mov.b64 %0, {%1, %2};" : "=l"(d) : "r"(lo), "r"(hi)); return d; }
__device__ __forceinline__ void mbar_init(uint32_t a, int c) { asm volatile("mbarrier.init.shared::cta.b64 [%0], %1;" :: "r"(a), "r"(c)); }
__device__ __forceinline__ void mbar_expect(uint32_t a, uint32_t b) { asm volatile("mbarrier.arrive.expect_tx.shared::cta.b64 _, [%0], %1;" :: "r"(a), "r"(b) : "memory"); }
__device__ __forceinline__ void mbar_arrive(uint32_t a) { asm volatile("mbarrier.arrive.shared::cta.b64 _, [%0];" :: "r"(a) : "memory"); }
#define TRACE(i)
#define TRW(i)
#define TR2(k, i)
#define SPIN_LIMIT (1 << 20)
#define SPIN_FAIL(code) __trap()
__device__ __forceinline__ void mbar_wait(uint32_t a, uint32_t ph) {
    asm volatile("{\n.reg .pred p, q;\n.reg .u32 c;\nmov.u32 c, 0;\n"
                 "W0:\nmbarrier.try_wait.parity.shared::cta.b64 p, [%0], %1;\n@p bra W1;\n"
                 "add.u32 c, c, 1;\nsetp.lt.u32 q, c, %2;\n@q bra W0;\ntrap;\n"
                 "W1:\n}" :: "r"(a), "r"(ph), "n"(4 * SPIN_LIMIT) : "memory");
}
__device__ __forceinline__ void mbar_sleep(uint32_t a, uint32_t ph) {
    asm volatile("{\n.reg .pred p, q;\n.reg .u32 c;\nmov.u32 c, 0;\n"
                 "W0:\nmbarrier.try_wait.parity.shared::cta.b64 p, [%0], %1, 4000;\n@p bra W1;\n"
                 "add.u32 c, c, 1;\nsetp.lt.u32 q, c, %2;\n@q bra W0;\ntrap;\n"
                 "W1:\n}" :: "r"(a), "r"(ph), "n"(SPIN_LIMIT) : "memory");
}
__device__ __forceinline__ uint32_t mbar_try(uint32_t a, uint32_t ph) {
    uint32_t ok;
    asm volatile("{\n.reg .pred p;\nmbarrier.test_wait.parity.shared::cta.b64 p, [%1], %2;\nselp.u32 %0, 1, 0, p;\n}" : "=r"(ok) : "r"(a), "r"(ph) : "memory");
    return ok;
}
__device__ __forceinline__ void wg_fence() { asm volatile("wgmma.fence.sync.aligned;" ::: "memory"); }
__device__ __forceinline__ void wg_commit() { asm volatile("wgmma.commit_group.sync.aligned;" ::: "memory"); }
template<int N> __device__ __forceinline__ void wg_wait() { asm volatile("wgmma.wait_group.sync.aligned %0;" :: "n"(N) : "memory"); }
__device__ __forceinline__ void bar_sync(int id, int n) { asm volatile("bar.sync %0, %1;" :: "r"(id), "r"(n) : "memory"); }
__device__ __forceinline__ void bar_arrive(int id, int n) { asm volatile("bar.arrive %0, %1;" :: "r"(id), "r"(n) : "memory"); }
__device__ __forceinline__ void fence_async() { asm volatile("fence.proxy.async.global;" ::: "memory"); }
__device__ __forceinline__ void flag_wait(int f, unsigned target) {
    const unsigned* p = &g_flags[f * 8];
    unsigned v;
    #pragma unroll 1
    for (int it = 0; it < SPIN_LIMIT; it++) {
        asm volatile("ld.acquire.gpu.global.u32 %0, [%1];" : "=r"(v) : "l"(p) : "memory");
        if (v >= target) return;
        __nanosleep(20);
    }
    SPIN_FAIL(f);
}
__device__ __forceinline__ void flag_add(int f) { asm volatile("red.release.gpu.global.add.u32 [%0], 1;" :: "l"(&g_flags[f * 8]) : "memory"); }
__device__ __forceinline__ void tma2d(uint32_t dst, const CUtensorMap* m, int c0, int c1, uint32_t bar) {
    asm volatile("cp.async.bulk.tensor.2d.shared::cluster.global.mbarrier::complete_tx::bytes [%0], [%1, {%3, %4}], [%2];"
        :: "r"(dst), "l"(m), "r"(bar), "r"(c0), "r"(c1) : "memory");
}
__device__ __forceinline__ void bulk_ld(uint32_t dst, const void* src, uint32_t bytes, uint32_t bar) {
    asm volatile("cp.async.bulk.shared::cluster.global.mbarrier::complete_tx::bytes [%0], [%1], %2, [%3];"
        :: "r"(dst), "l"(src), "r"(bytes), "r"(bar) : "memory");
}
__device__ __forceinline__ void tma3d_mc(uint32_t dst, const CUtensorMap* m, int c1, int c2, uint32_t bar) {
    asm volatile("cp.async.bulk.tensor.3d.shared::cluster.global.mbarrier::complete_tx::bytes.multicast::cluster [%0], [%1, {0, %3, %4}], [%2], %5;"
        :: "r"(dst), "l"(m), "r"(bar), "r"(c1), "r"(c2), "h"((uint16_t)3) : "memory");
}
__device__ __forceinline__ void bulk_ld_mc(uint32_t dst, const void* src, uint32_t bytes, uint32_t bar) {
    asm volatile("cp.async.bulk.shared::cluster.global.mbarrier::complete_tx::bytes.multicast::cluster [%0], [%1], %2, [%3], %4;"
        :: "r"(dst), "l"(src), "r"(bytes), "r"(bar), "h"((uint16_t)3) : "memory");
}
__device__ __forceinline__ void release2(uint32_t a, uint32_t peer_off) {
    asm volatile("mbarrier.arrive.shared::cta.b64 _, [%0];\nmbarrier.arrive.shared::cluster.b64 _, [%1];" :: "r"(a), "r"(a + peer_off) : "memory");
}
__device__ __forceinline__ void release2n(uint32_t a, uint32_t pa, uint32_t cnt) {
    asm volatile("{\n.reg .pred p;\nsetp.ne.u32 p, %2, 0;\n@p mbarrier.arrive.shared::cta.b64 _, [%0], %2;\n@p mbarrier.arrive.shared::cluster.b64 _, [%1], %2;\n}"
                 :: "r"(a), "r"(pa), "r"(cnt) : "memory");
}
__device__ __forceinline__ void cluster_sync() { asm volatile("barrier.cluster.arrive.release;\nbarrier.cluster.wait.acquire;" ::: "memory"); }
__device__ __forceinline__ void l2_prefetch(const void* src, uint32_t bytes) {
    asm volatile("cp.async.bulk.prefetch.L2.global [%0], %1;" :: "l"(src), "r"(bytes) : "memory");
}
__device__ __forceinline__ uint32_t pack_bf16(float lo, float hi) { uint32_t r; asm("cvt.rn.bf16x2.f32 %0, %1, %2;" : "=r"(r) : "f"(hi), "f"(lo)); return r; }
__device__ __forceinline__ float bf_lo(uint32_t v) { return __uint_as_float(v << 16); }
__device__ __forceinline__ float bf_hi(uint32_t v) { return __uint_as_float(v & 0xFFFF0000u); }
__device__ __forceinline__ float gelu2_tanh(float x) {
    float u = x * fmaf(x * x, 0.0356774081363001f, 0.7978845608028654f), t;
    asm("tanh.approx.f32 %0, %1;" : "=f"(t) : "f"(u));
    return fmaf(x, t, x);
}
#define FENCE_F(a, n) _Pragma("unroll") for (int i_ = 0; i_ < n; i_++) asm volatile("" : "+f"(a[i_]) :: "memory");
#define FENCE_R(a, n) _Pragma("unroll") for (int i_ = 0; i_ < n; i_++) asm volatile("" : "+r"(a[i_]) :: "memory");

__device__ __forceinline__ uint32_t exp2_mufu(float a, float b) {
    float x, y;
    asm("ex2.approx.ftz.f32 %0, %1;" : "=f"(x) : "f"(a));
    asm("ex2.approx.ftz.f32 %0, %1;" : "=f"(y) : "f"(b));
    return pack_bf16(x, y);
}
__device__ __forceinline__ uint32_t exp2_alu(float a, float b, uint32_t half2c) {
    uint32_t L = __byte_perm(__float_as_uint(a), __float_as_uint(b), 0x6521), G, r;
    asm("lop3.b32 %0, %1, 0x007F007F, %2, 0xEA;" : "=r"(G) : "r"(L), "r"(half2c));
    uint32_t E = L & 0xFF80FF80u;
    asm("fma.rn.bf16x2 %0, %1, %2, %3;" : "=r"(r) : "r"(G), "r"(L), "r"(E));
    return r;
}
#define EXPBLK(p, s) _Pragma("unroll") for (int b = 0; b < 8; b++) { \
    if ((PAT >> b) & 1) { p[2*b] = exp2_alu(s[4*b], s[4*b+1], half2c); p[2*b+1] = exp2_alu(s[4*b+2], s[4*b+3], half2c); } \
    else { p[2*b] = exp2_mufu(s[4*b], s[4*b+1]); p[2*b+1] = exp2_mufu(s[4*b+2], s[4*b+3]); } }

struct Ring { uint32_t st, ph; };
template<int NST> __device__ __forceinline__ void ring_next(Ring& r) { if (++r.st == NST) { r.st = 0; r.ph ^= 1; } }

struct OpDesc { uint32_t lo, hi, step, step2, nsplit; };

template<int N, int PART> __device__ __forceinline__ void wgmma_ss(float (&d)[N / 2], uint64_t da, uint64_t db, int sc) {
    if constexpr (N == 160) {
        if constexpr (PART == 0) wgmma_ss_n96<0, 1>(*(float(*)[48])&d[0], da, db, sc);
        else wgmma_ss_n64<0, 1>(*(float(*)[32])&d[48], da, db, sc);
    } else {
        if constexpr (PART == 0) wgmma_ss_n128<0, 1>(*(float(*)[64])&d[0], da, db, sc);
        else wgmma_ss_n96<0, 1>(*(float(*)[48])&d[64], da, db, sc);
    }
}

struct GemmCtx { Ring r; uint32_t sb16, bar_full, bar_empty, peer_off; bool lead; };

template<int N, int NS, int GB>
__device__ __forceinline__ void gemm_loop(float (&acc)[N / 2], int nkb, int first, OpDesc a, OpDesc b, GemmCtx& c) {
    uint32_t prev = 0;
    #pragma unroll 1
    for (int kb = 0; kb < nkb; kb++) {
        mbar_sleep(c.bar_full + 8 * c.r.st, c.r.ph);
        const uint32_t base = c.sb16 + c.r.st * (GST_BYTES / 16);
        const uint64_t da0 = mkdesc(base + a.lo, a.hi), db0 = mkdesc(base + b.lo, b.hi);
        wg_fence();
        #pragma unroll
        for (int k = 0; k < NS; k++) {
            const uint64_t da = da0 + k * a.step, db = db0 + ((k & 1) * b.step + (k >> 1) * b.step2);
            const int sc = (k > 0) | (kb > 0) | !first;
            wgmma_ss<N, 0>(acc, da, db, sc);
            if constexpr (GB > 0) { wg_commit(); wg_wait<GB - 1>(); }
            wgmma_ss<N, 1>(acc, da, db + b.nsplit, sc);
            if constexpr (GB < 0) {
                if ((k + 1) % (-GB) == 0 || k == NS - 1) {
                    wg_commit(); wg_wait<1>();
                    if (k < -GB && kb > 0 && c.lead) release2(c.bar_empty + 8 * prev, c.peer_off);
                }
            }
            if constexpr (GB > 0) {
                wg_commit(); wg_wait<GB - 1>();
                if (k == (GB - 1) / 2 && kb > 0 && c.lead) release2(c.bar_empty + 8 * prev, c.peer_off);
            }
        }
        if constexpr (GB == 0) {
            wg_commit();
            wg_wait<1>();
            if (kb > 0 && c.lead) release2(c.bar_empty + 8 * prev, c.peer_off);
        }
        prev = c.r.st;
        ring_next<GST>(c.r);
    }
    wg_wait<0>();
    if (c.lead) release2(c.bar_empty + 8 * prev, c.peer_off);
    FENCE_F(acc, N / 2);
}

template<int CNT, int SUBS>
__device__ __forceinline__ void retile_ld(uint4 (&v)[CNT], const __nv_bfloat16* src, int pitch, int ncg, int nkg, int cm0, int cnt, int id) {
    const int sub = id >> 3, row = id & 7;
    #pragma unroll
    for (int i = 0; i < CNT; i++) {
        const int l = sub + i * SUBS, cm = cm0 + l, kg = cm / ncg, cg = cm - kg * ncg;
        if (l < cnt && kg < nkg) v[i] = __ldg((const uint4*)(src + (size_t)(kg * 8 + row) * pitch + cg * 8));
    }
}
template<int NG, int CNT, int SUBS, bool PERM>
__device__ __forceinline__ void retile_st(const uint4 (&v)[CNT], int ncg, int nkg, uint8_t* dst, int cm0, int cnt, int id) {
    const int sub = id >> 3, row = id & 7;
    #pragma unroll
    for (int i = 0; i < CNT; i++) {
        const int l = sub + i * SUBS, cm = cm0 + l, kg = cm / ncg, cg = cm - kg * ncg, tile = cg / NG;
        int kd = kg;
        if (PERM) { const int q = kg / 20, rem = kg - q * 20; kd = rem < 4 ? q * 4 + rem : (rem < 12 ? 12 + q * 8 + rem : 36 + q * 8 + rem); }
        if (l < cnt && kg < nkg) *(uint4*)(dst + (size_t)((tile * nkg + kd) * NG + (cg - tile * NG)) * 128 + row * 16) = v[i];
    }
}

__global__ void __cluster_dims__(2, 1, 1) __launch_bounds__(640, 1) mega_kernel(const __grid_constant__ Params p) {
    extern __shared__ uint8_t smem_raw[];
    if (threadIdx.x == 0) TRW(31);
    const uint32_t sb = ((uint32_t)__cvta_generic_to_shared(smem_raw) + 1023u) & ~1023u;
    uint8_t* sm = smem_raw + (sb - (uint32_t)__cvta_generic_to_shared(smem_raw));
    const uint32_t bar_gfull = sb + SM_MISC, bar_gempty = bar_gfull + 64, bar_kfull = bar_gfull + 128, bar_kempty = bar_gfull + 192;
    float* s_gate = (float*)(sm + SM_MISC + 256);
    float* s_stat = (float*)(sm + SM_MISC + 512);
    float* s_red = (float*)(sm + SM_MISC + 768);
    float* s_ln = (float*)(sm + SM_MISC + 1024);
    const int rb = blockIdx.x & 31, ct = blockIdx.x >> 5;
    const int rank = rb & 1;
    const int wg = __shfl_sync(0xffffffffu, threadIdx.x >> 7, 0);
    const int tid = threadIdx.x & 127, w = tid >> 5, lane = tid & 31, g = lane >> 2, t = lane & 3;
    uint32_t peer_off;
    asm("mapa.shared::cluster.u32 %0, %1, %2;" : "=r"(peer_off) : "r"(sb), "r"(rank ^ 1));
    peer_off -= sb;

    if (threadIdx.x == 32) {
        l2_prefetch(p.wq + (size_t)blockIdx.x * 3200, 6400);
        l2_prefetch(p.win + (size_t)blockIdx.x * 8640, 17280);
    }
    if (threadIdx.x == 0) {
        for (int i = 0; i < GST; i++) { mbar_init(bar_gfull + 8 * i, 1); mbar_init(bar_gempty + 8 * i, 8); }
        for (int i = 0; i < KST; i++) { mbar_init(bar_kfull + 8 * i, 1); mbar_init(bar_kempty + 8 * i, 24); }
        mbar_init(bar_kfull + 32, 1); mbar_init(bar_kfull + 40, 1);
        asm volatile("fence.mbarrier_init.release.cluster;" ::: "memory");
        asm volatile("fence.proxy.async.shared::cta;" ::: "memory");
    }
    cluster_sync();

    if (wg == 4) {
        asm volatile("setmaxnreg.dec.sync.aligned.u32 24;");
        static_assert(GST == 4, "ring indices are derived from a running stage counter");
        #define STG_ADDR(n) (sb + SM_G + ((n) & 3) * GST_BYTES)
        #define STG_FULL(n) (bar_gfull + ((n) & 3) * 8)
        #define STG_WAIT(n) mbar_sleep(bar_gempty + ((n) & 3) * 8, (((n) >> 2) & 1) ^ 1)
        const uint32_t n0 = ct < 2 ? 3 : 0;
        if (w == 0) {
            uint32_t n = n0;
            if (lane == 0) {
                #pragma unroll 1
                for (int kb = 0; kb < 10; kb++, n++) {
                    STG_WAIT(n);
                    mbar_expect(STG_FULL(n), 8192 + 20480);
                    tma3d_mc(STG_ADDR(n) + 8192 + rank * 10240, &p.mwq, kb * 64 + rank * 32, 5 * ct, STG_FULL(n));
                }
                #pragma unroll 1
                for (int i = 0; i < 20; i++, n++) {
                    STG_WAIT(n);
                    mbar_expect(STG_FULL(n), 8192 + 28672);
                    tma3d_mc(STG_ADDR(n) + 8192 + rank * 14336, &p.mwin, (i < 10 ? i : i - 10) * 64 + rank * 32, (i < 10 ? 27 : 0) + 7 * ct, STG_FULL(n));
                }
            }
            __syncwarp();
            #pragma unroll 1
            for (int it = 0; ; it++) {
                unsigned v;
                asm volatile("ld.acquire.gpu.global.u32 %0, [%1];" : "=r"(v) : "l"(&g_flags[(F_Z2 + lane * 4 + ct) * 8]) : "memory");
                if (__all_sync(0xffffffffu, v != 0)) break;
                if (it > SPIN_LIMIT) SPIN_FAIL(F_Z2);
                __nanosleep(20);
            }
            if (lane == 0) {
                fence_async();
                const uint8_t* src = g_z2n + (size_t)ct * 32 * 28672 + rank * 14336;
                #pragma unroll 1
                for (int kb = 0; kb < 32; kb++, n++, src += 28672) {
                    STG_WAIT(n);
                    mbar_expect(STG_FULL(n), 8192 + 28672);
                    bulk_ld_mc(STG_ADDR(n) + 8192 + rank * 14336, src, 14336, STG_FULL(n));
                }
                flag_wait(F_WR, NCTA / 2);
                fence_async();
                n++;
                #pragma unroll 1
                for (int i = 0; i < 2; i++, n++) {
                    STG_WAIT(n);
                    mbar_expect(STG_FULL(n), 28672);
                    bulk_ld_mc(STG_ADDR(n) + 8192 + rank * 10240, g_wot + (size_t)(ct * 80 + i * 8) * 2560 + rank * 10240, 10240, STG_FULL(n));
                }
                uint32_t k0 = 28 * ct + rank * 4;
                #pragma unroll 1
                for (int i = 0; i < 14; i++, n++) {
                    const uint32_t nk = i == 13 ? 2 : 4;
                    if (i == 13) k0 -= rank * 2;
                    if (k0 >= 108) k0 -= 108;
                    STG_WAIT(n);
                    mbar_expect(STG_FULL(n), nk * 2 * (2560 + 1024));
                    bulk_ld_mc(STG_ADDR(n) + 8192 + rank * nk * 2560, g_woutt + (size_t)(ct * 108 + k0) * 2560, nk * 2560, STG_FULL(n));
                    k0 += 8;
                }
                #pragma unroll 1
                for (int i = 2; i < 10; i++, n++) {
                    STG_WAIT(n);
                    mbar_expect(STG_FULL(n), 28672);
                    bulk_ld_mc(STG_ADDR(n) + 8192 + rank * 10240, g_wot + (size_t)(ct * 80 + i * 8) * 2560 + rank * 10240, 10240, STG_FULL(n));
                }
            }
        } else if (w == 3) {
            if (lane == 0) {
                if (ct < 2) {
                    #pragma unroll 1
                    for (int kb = 0; kb < 10; kb++) {
                        if ((kb & 3) == 0) mbar_expect(STG_FULL(kb >> 2), kb < 8 ? 32768 : 16384);
                        tma2d(STG_ADDR(kb >> 2) + (kb & 3) * 8192, &p.mx, kb * 64, rb * 64, STG_FULL(kb >> 2));
                    }
                }
                uint32_t n = n0;
                #pragma unroll 1
                for (int j = 0; j < 3; j++) {
                    #pragma unroll 1
                    for (int kb = 0; kb < 10; kb++, n++) {
                        STG_WAIT(n);
                        tma2d(STG_ADDR(n), &p.mx, kb * 64, rb * 64, STG_FULL(n));
                        if (j > 0 && kb >= 2) l2_prefetch(p.wsp + (size_t)(rb * 64 + ct * 16 + (j - 1) * 8 + kb - 2) * S_LEN, 4096);
                    }
                }
                #define STASH_STAGE(which) { STG_WAIT(n); fence_async(); mbar_expect(STG_FULL(n), 28672); \
                    bulk_ld(STG_ADDR(n), g_z1 + (size_t)((which) * NCTA + blockIdx.x) * 1792, 28672, STG_FULL(n)); n++; }
                #pragma unroll 1
                for (int kb = 0; kb < 32; kb++, n++) {
                    STG_WAIT(n);
                    tma2d(STG_ADDR(n), &p.mwsp, kb * 64, rb * 64, STG_FULL(n));
                }
                STASH_STAGE(0)
                const uint8_t* op = g_op + (size_t)rb * 80 * 1024;
                const uint8_t* hp = g_hp + (size_t)rb * 108 * 1024;
                flag_wait(F_O + rb * 3, 4);
                fence_async();
                #pragma unroll 1
                for (int i = 0; i < 2; i++, n++) { STG_WAIT(n); bulk_ld(STG_ADDR(n), op + i * 8192, 8192, STG_FULL(n)); }
                mbar_sleep(bar_kfull + 40, 0);
                fence_async();
                uint32_t k0 = 28 * ct;
                #pragma unroll 1
                for (int i = 0; i < 14; i++, n++) {
                    if (i == 3) { flag_wait(F_H + rb, 4); fence_async(); }
                    STG_WAIT(n);
                    const uint32_t nb = (i == 13 || k0 == 104) ? 4096 : 8192;
                    bulk_ld(STG_ADDR(n), hp + k0 * 1024, nb, STG_FULL(n));
                    if (k0 == 104 && i != 13) bulk_ld(STG_ADDR(n) + 4096, hp, 4096, STG_FULL(n));
                    k0 += 8; if (k0 >= 108) k0 -= 108;
                }
                #pragma unroll 1
                for (int i = 2; i < 10; i++, n++) {
                    if (i == 2 || i == 6) { flag_wait(F_O + rb * 3 + (i == 2 ? 1 : 2), i == 2 ? 4 : 12); fence_async(); }
                    STG_WAIT(n);
                    bulk_ld(STG_ADDR(n), op + i * 8192, 8192, STG_FULL(n));
                }
            }
        } else if (w == 1) {
            if (lane == 0) {
                flag_wait(F_KV, 64);
                asm volatile("fence.proxy.async.global;" ::: "memory");
                TRW(19);
                mbar_expect(bar_kfull + 32, 3072 + 512);
                bulk_ld(sb + SM_KV + 3 * KST_BYTES + 6144, g_kv + 31 * 6144, 3072, bar_kfull + 32);
                bulk_ld(sb + SM_MISC + 512, g_kvmax, 256, bar_kfull + 32);
                bulk_ld(sb + SM_MISC + 256, g_gate + rb * 64, 256, bar_kfull + 32);
                #pragma unroll 1
                for (int i = 0; i < 48; i++) {
                    const uint32_t st = i & 3;
                    if (i >= 3) mbar_sleep(bar_kempty + 8 * st, (((i + 1) >> 2) & 1) ^ 1);
                    mbar_expect(bar_kfull + 8 * st, KST_BYTES);
                    bulk_ld_mc(sb + SM_KV + st * KST_BYTES + rank * 6144, g_kv + (i & 15) * KST_BYTES + rank * 6144, 6144, bar_kfull + 8 * st);
                    if (i == 19 || i == 35) flag_add(F_O + rb * 3 + (i == 35));
                }
            }
        } else {
            if (ct < 2) {
                bar_sync(10, 160);
                if (lane == 0) {
                    uint32_t m = max(max(__float_as_uint(s_red[8]), __float_as_uint(s_red[9])), max(__float_as_uint(s_red[10]), __float_as_uint(s_red[11])));
                    g_kvmax[ct * 32 + rb] = __uint_as_float(m);
                    flag_add(F_KV);
                }
                __syncwarp();
            }
            bar_sync(10, 160);
            if (lane == 0) { flag_add(F_H + rb); mbar_arrive(bar_kfull + 40); }
        }
    } else if (wg == 3) {
        asm volatile("setmaxnreg.inc.sync.aligned.u32 144;");
        TRACE(0);
        GemmCtx c{{0, 0}, ((sb + SM_G) & 0x3FFFFu) >> 4, bar_gfull, bar_gempty, peer_off, lane == 0};
        const OpDesc a_sw{0u, 64u | (1u << 30), 2u, 0u, 0u};
        const OpDesc a_t{64u << 16, 8u, 128u, 0u, 0u};
        const OpDesc b_q{512u | (128u << 16), 32u | (2u << 30), 64u, 640u, 384u};
        const OpDesc b_w{512u | (128u << 16), 32u | (2u << 30), 64u, 896u, 512u};
        const OpDesc b_z{512u | (224u << 16), 8u, 448u, 896u, 128u};
        const OpDesc b_o{512u | (160u << 16), 8u, 320u, 640u, 96u};
        const int r0 = 16 * w + g;
        if (ct < 2) {
            float ex[12];
            const uint32_t exlo = (((sb + SM_KV) & 0x3FFFFu) >> 4) | (24u << 16);
            bar_sync(1, 512);
            #pragma unroll 1
            for (int kb = 0; kb < 10; kb++) {
                if ((kb & 3) == 0) mbar_wait(bar_gfull + 8 * (kb >> 2), 0);
                const uint32_t base = c.sb16 + (kb >> 2) * (GST_BYTES / 16) + (kb & 3) * 512;
                wg_fence();
                #pragma unroll
                for (int k = 0; k < 4; k++) wgmma_ss_n24<0, 1>(ex, mkdesc(base + 2 * k, a_sw.hi), mkdesc(exlo + (kb * 4 + k) * 48, 8), (k > 0) | (kb > 0));
                wg_commit();
            }
            wg_wait<0>();
            FENCE_F(ex, 12);
            if (lane < 3) release2(bar_gempty + 8 * lane, peer_off);
            c.r.st = 3;
            uint8_t* dst = g_kv + (ct == 0 ? (rb + 31) & 31 : rb) * 6144 + ct * 3072 + 2 * w * 384 + g * 16 + t * 4;
            float mx = 0.f;
            #pragma unroll
            for (int hi = 0; hi < 2; hi++) {
                const bool alu = (PAT >> (2 * w + hi)) & 1;
                float n2 = 0.f;
                #pragma unroll
                for (int j = 0; j < 3; j++) {
                    uint32_t v = pack_bf16(ex[4 * j + 2 * hi], ex[4 * j + 2 * hi + 1]);
                    float a = bf_lo(v), b = bf_hi(v);
                    if (ct == 0) {
                        n2 = fmaf(a, a, fmaf(b, b, n2));
                        if (alu) v = pack_bf16(2.f * a, 2.f * b);
                        if (j == 2 && t == 2) v = alu ? 0x3C004440u : 0x39A93FCBu;
                    } else {
                        if (j < 2 || t < 2) n2 = __uint_as_float(max(__float_as_uint(n2), max(__float_as_uint(fabsf(a)), __float_as_uint(fabsf(b)))));
                        if (j == 2 && t == 3) {
                            g_gate[rb * 64 + r0 + 8 * hi] = 1.f / (1.f + __expf(-ex[8 + 2 * hi]));
                            v = 0u;
                        }
                        if (j == 2 && t == 2) v = 0x00003F80u;
                    }
                    *(uint32_t*)(dst + hi * 384 + j * 128) = v;
                }
                if (ct == 0) { n2 += __shfl_xor_sync(0xffffffffu, n2, 1); n2 += __shfl_xor_sync(0xffffffffu, n2, 2); }
                mx = __uint_as_float(max(__float_as_uint(mx), __float_as_uint(n2) & 0x7FFFFFFFu));
            }
            mx = __uint_as_float(__reduce_max_sync(0xffffffffu, __float_as_uint(mx)));
            if (lane == 0) s_red[8 + w] = mx;
            bar_arrive(10, 160);
            TRACE(15);
        }
        {
            float acc[80];
            gemm_loop<160, 4, 0>(acc, 10, 1, a_sw, b_q, c);
            TRACE(1);
            uint8_t* qs = sm + SM_Q + 2 * w * 128 + g * 16;
            #pragma unroll
            for (int j = 0; j < 20; j++) {
                constexpr int dummy = 0; (void)dummy;
                const int h0 = (8 * j) / 20, d0 = (8 * j) % 20, d = d0 + 2 * t;
                const int off = d < 20 ? h0 * 3072 + (d >> 3) * 1024 + (d & 7) * 2 : (h0 + 1) * 3072 + (d - 20) * 2;
                *(uint32_t*)(qs + off) = pack_bf16(acc[4 * j] * 0.3225964182229561f, acc[4 * j + 1] * 0.3225964182229561f);
                *(uint32_t*)(qs + off + 128) = pack_bf16(acc[4 * j + 2] * 0.3225964182229561f, acc[4 * j + 3] * 0.3225964182229561f);
            }
            bar_arrive(2, 384);
            bar_arrive(13, 256);
        }
        {
            float acc[112];
            gemm_loop<224, 4, GB2>(acc, 10, 1, a_sw, b_w, c);
            TRACE(2);
            uint4* z1p = g_z1 + (size_t)blockIdx.x * 14 * 128 + tid;
            {
                float s0 = 0.f, q0 = 0.f, s1 = 0.f, q1 = 0.f;
                #pragma unroll
                for (int j = 0; j < 14; j++) {
                    float y[8];
                    #pragma unroll
                    for (int i = 0; i < 8; i++) y[i] = gelu2_tanh(acc[8 * j + i]);
                    s0 += (y[0] + y[1]) + (y[4] + y[5]); q0 = fmaf(y[0], y[0], fmaf(y[1], y[1], fmaf(y[4], y[4], fmaf(y[5], y[5], q0))));
                    s1 += (y[2] + y[3]) + (y[6] + y[7]); q1 = fmaf(y[2], y[2], fmaf(y[3], y[3], fmaf(y[6], y[6], fmaf(y[7], y[7], q1))));
                    z1p[(NCTA * 14 + j) * 128] = make_uint4(pack_bf16(y[0], y[1]), pack_bf16(y[2], y[3]), pack_bf16(y[4], y[5]), pack_bf16(y[6], y[7]));
                }
                #pragma unroll
                for (int o = 1; o <= 2; o <<= 1) {
                    s0 += __shfl_xor_sync(0xffffffffu, s0, o); q0 += __shfl_xor_sync(0xffffffffu, q0, o);
                    s1 += __shfl_xor_sync(0xffffffffu, s1, o); q1 += __shfl_xor_sync(0xffffffffu, q1, o);
                }
                if (t < 2) asm volatile("st.relaxed.gpu.global.v4.u32 [%0], {%1, %2, %3, %3};" :: "l"(&g_part[(rb * 4 + ct) * 64 + r0 + 8 * t]),
                                        "r"(__float_as_uint(t ? s1 : s0)), "r"(__float_as_uint(t ? q1 : q0)), "r"(1u) : "memory");
            }
            bar_arrive(11, 256);
            TRACE(3);
            gemm_loop<224, 4, GB3>(acc, 10, 1, a_sw, b_w, c);
            TRACE(4);
            #pragma unroll
            for (int j = 0; j < 14; j++)
                z1p[j * 128] = make_uint4(pack_bf16(gelu2_tanh(acc[8 * j]), gelu2_tanh(acc[8 * j + 1])), pack_bf16(gelu2_tanh(acc[8 * j + 2]), gelu2_tanh(acc[8 * j + 3])),
                                          pack_bf16(gelu2_tanh(acc[8 * j + 4]), gelu2_tanh(acc[8 * j + 5])), pack_bf16(gelu2_tanh(acc[8 * j + 6]), gelu2_tanh(acc[8 * j + 7])));
            TRACE(7);
            const float b0 = __bfloat162float(p.bsp[rb * 64 + r0]), b1 = __bfloat162float(p.bsp[rb * 64 + r0 + 8]);
            gemm_loop<224, 4, GB4>(acc, 32, 1, a_sw, b_z, c);
            TRACE(8);
            bar_sync(8, 512);
            const float g0 = 0.5f - 0.5f * s_gate[r0], g1 = 0.5f - 0.5f * s_gate[r0 + 8];
            {
                mbar_wait(c.bar_full + 8 * c.r.st, c.r.ph);
                const uint4* zs = (const uint4*)(sm + SM_G + c.r.st * GST_BYTES) + tid;
                uint8_t* dst = g_hp + (size_t)((rb * 108 + 28 * ct) * 8 + 2 * w) * 128 + g * 16 + t * 4;
                const float e0 = b0 * g0, e1 = b1 * g1;
                #pragma unroll
                for (int j = 0; j < 14; j++) {
                    if (j < 12 || ct < 3) {
                        const uint4 v = zs[j * 128];
                        *(uint32_t*)(dst + (2 * j) * 1024) = pack_bf16(fmaf(acc[8 * j], g0, e0) * bf_lo(v.x), fmaf(acc[8 * j + 1], g0, e0) * bf_hi(v.x));
                        *(uint32_t*)(dst + (2 * j) * 1024 + 128) = pack_bf16(fmaf(acc[8 * j + 2], g1, e1) * bf_lo(v.y), fmaf(acc[8 * j + 3], g1, e1) * bf_hi(v.y));
                        *(uint32_t*)(dst + (2 * j + 1) * 1024) = pack_bf16(fmaf(acc[8 * j + 4], g0, e0) * bf_lo(v.z), fmaf(acc[8 * j + 5], g0, e0) * bf_hi(v.z));
                        *(uint32_t*)(dst + (2 * j + 1) * 1024 + 128) = pack_bf16(fmaf(acc[8 * j + 6], g1, e1) * bf_lo(v.w), fmaf(acc[8 * j + 7], g1, e1) * bf_hi(v.w));
                    }
                }
                __syncwarp();
                if (c.lead) release2(c.bar_empty + 8 * c.r.st, c.peer_off);
                ring_next<GST>(c.r);
            }
            bar_arrive(10, 160);
            TRACE(9);
        }
        {
            float acc[80];
            gemm_loop<160, 4, GB5>(acc, 15, 1, a_t, b_o, c);
            gemm_loop<160, 2, GB5>(acc, 1, 0, a_t, b_o, c);
            gemm_loop<160, 4, GB5>(acc, 4, 0, a_t, b_o, c);
            TRACE(10);
            gemm_loop<160, 4, 0>(acc, 4, 0, a_t, b_o, c);
            TRACE(11);
            uint32_t* os = (uint32_t*)(sm + SM_Q) + r0 * (QS_PITCH / 2) + t;
            #pragma unroll
            for (int j = 0; j < 20; j++) {
                os[4 * j] = pack_bf16(acc[4 * j], acc[4 * j + 1]);
                os[8 * (QS_PITCH / 2) + 4 * j] = pack_bf16(acc[4 * j + 2], acc[4 * j + 3]);
            }
            asm volatile("fence.proxy.async.shared::cta;" ::: "memory");
            __syncwarp();
            if (lane < 16) {
                const int row = 16 * w + lane;
                asm volatile("cp.async.bulk.global.shared::cta.bulk_group [%0], [%1], 320;"
                             :: "l"(p.out + (size_t)(rb * 64 + row) * DM + 160 * ct), "r"(sb + SM_Q + row * (QS_PITCH * 2)) : "memory");
                asm volatile("cp.async.bulk.commit_group;\ncp.async.bulk.wait_group 0;" ::: "memory");
            }
            TRACE(12);
            if (tid < 64) g_part[(rb * 4 + ct) * 64 + tid] = make_uint4(0u, 0u, 0u, 0u);
            if (tid == 0) {
                unsigned d = atomicAdd(&g_flags[F_DONE * 8], 1u);
                if (d == NCTA - 1) { for (int i = 0; i < F_NUM; i++) g_flags[i * 8] = 0; }
            }
            __syncwarp();
            cluster_sync();
            TRACE(20);
        }
    } else {
        asm volatile("setmaxnreg.inc.sync.aligned.u32 104;");
        const int atid = threadIdx.x;
        {
            *(uint2*)(sm + SM_Q + 8 * 3072 + (atid & 127) * 8) = make_uint2(0u, 0u);
            if (ct >= 2) {
                uint4 w1[3], w2[3];
                const int c1 = (blockIdx.x & 63) * 100, c2 = (blockIdx.x & 63) * 135;
                retile_ld<3, 48>(w1, p.wo, DM, 80, 80, c1, 100, atid);
                retile_ld<3, 48>(w2, p.wout, DM, 80, 108, c2, 135, atid);
                retile_st<20, 3, 48, true>(w1, 80, 80, g_wot, c1, 100, atid);
                retile_st<20, 3, 48, false>(w2, 80, 108, g_woutt, c2, 135, atid);
                bar_sync(9, 384);
                if (atid == 256) flag_add(F_WR);
            } else if (wg == 2) {
                bar_arrive(1, 512);
            } else {
                const int q = atid & 3, k0 = atid >> 2;
                const uint32_t dst = sb + SM_KV + (k0 >> 3) * 384 + (k0 & 7) * 16 + q * 4;
                const uint32_t* src = (const uint32_t*)(ct == 0 ? p.wk : p.wv) + k0 * 10 + q;
                uint32_t gv[10];
                #pragma unroll 1
                for (int i = 0; i < 10; i++) {
                    asm volatile("cp.async.ca.shared.global [%0], [%1], 4;\ncp.async.ca.shared.global [%0+128], [%1+16], 4;" :: "r"(dst + i * 3072), "l"(src + i * 640) : "memory");
                    if (q < 2) asm volatile("cp.async.ca.shared.global [%0+256], [%1+32], 4;" :: "r"(dst + i * 3072), "l"(src + i * 640) : "memory");
                }
                #pragma unroll
                for (int i = 0; i < 10; i++) gv[i] = (q == 3 && ct == 1) ? (uint32_t)__ldg((const unsigned short*)p.gw + k0 + 64 * i) : 0u;
                if (q >= 2) {
                    #pragma unroll
                    for (int i = 0; i < 10; i++) asm volatile("st.shared.u32 [%0], %1;" :: "r"(dst + i * 3072 + 256), "r"(gv[i]) : "memory");
                }
                asm volatile("cp.async.wait_all;" ::: "memory");
                asm volatile("fence.proxy.async.shared::cta;" ::: "memory");
                bar_arrive(1, 512);
                if (wg == 0) TRACE(13);
            }
        }
        const uint32_t half2c = *(const volatile uint32_t*)&g_const[2];
        if (wg == 2) {
            const int r0 = 16 * w + g;
            uint4* z1p = g_z1 + (size_t)blockIdx.x * 14 * 128 + tid;
            uint4 v[14];
            bar_sync(11, 256);
            #pragma unroll
            for (int j = 0; j < 14; j++) v[j] = __ldcg(z1p + (NCTA * 14 + j) * 128);
            float s0, q0, s1, q1;
            {
                uint4 a, b;
                const uint4* pa_ = &g_part[(rb * 4 + t) * 64 + r0];
                #pragma unroll 1
                for (int it = 0; ; it++) {
                    asm volatile("ld.relaxed.gpu.global.v4.u32 {%0, %1, %2, %3}, [%4];" : "=r"(a.x), "=r"(a.y), "=r"(a.z), "=r"(a.w) : "l"(pa_) : "memory");
                    asm volatile("ld.relaxed.gpu.global.v4.u32 {%0, %1, %2, %3}, [%4];" : "=r"(b.x), "=r"(b.y), "=r"(b.z), "=r"(b.w) : "l"(pa_ + 8) : "memory");
                    if (__all_sync(0xffffffffu, (a.z & b.z) != 0)) break;
                    if (it > SPIN_LIMIT) SPIN_FAIL(F_STAT);
                    __nanosleep(100);
                }
                s0 = __uint_as_float(a.x); q0 = __uint_as_float(a.y); s1 = __uint_as_float(b.x); q1 = __uint_as_float(b.y);
                #pragma unroll
                for (int o = 1; o <= 2; o <<= 1) {
                    s0 += __shfl_xor_sync(0xffffffffu, s0, o); q0 += __shfl_xor_sync(0xffffffffu, q0, o);
                    s1 += __shfl_xor_sync(0xffffffffu, s1, o); q1 += __shfl_xor_sync(0xffffffffu, q1, o);
                }
            }
            TRACE(5);
            const float m0 = s0 * (1.f / FH), m1 = s1 * (1.f / FH);
            const float rs0 = rsqrtf(fmaxf(q0 * (1.f / FH) - m0 * m0, 0.f) + 4e-5f), rs1 = rsqrtf(fmaxf(q1 * (1.f / FH) - m1 * m1, 0.f) + 4e-5f);
            const float c0 = -m0 * rs0, c1 = -m1 * rs1;
            uint8_t* dst = g_z2n + (size_t)(ct * 32 + rb) * 28672 + (2 * w) * 3584 + g * 16 + t * 4;
            #pragma unroll
            for (int j = 0; j < 14; j++) {
                *(uint32_t*)(dst + 2 * j * 128) = pack_bf16(fmaf(bf_lo(v[j].x), rs0, c0), fmaf(bf_hi(v[j].x), rs0, c0));
                *(uint32_t*)(dst + 3584 + 2 * j * 128) = pack_bf16(fmaf(bf_lo(v[j].y), rs1, c1), fmaf(bf_hi(v[j].y), rs1, c1));
                *(uint32_t*)(dst + (2 * j + 1) * 128) = pack_bf16(fmaf(bf_lo(v[j].z), rs0, c0), fmaf(bf_hi(v[j].z), rs0, c0));
                *(uint32_t*)(dst + 3584 + (2 * j + 1) * 128) = pack_bf16(fmaf(bf_lo(v[j].w), rs1, c1), fmaf(bf_hi(v[j].w), rs1, c1));
            }
            bar_sync(6, 128);
            if (tid == 0) flag_add(F_Z2 + rb * 4 + ct);
            TRACE(6);
            TRACE(14);
        }
        if (wg == 2) bar_sync(13, 256); else bar_sync(2, 384);
        const int p0 = wg == 2 ? 1 : 0;
        #define HEAD(ps) ((ps) == 0 ? wg : 3 * (ps) - 1 + wg)
        uint32_t qmax2 = 0;
        #pragma unroll 1
        for (int i = p0 + (tid >> 6); i < 3; i += 2) {
            uint8_t* qrow = sm + SM_Q + HEAD(i) * 3072 + (tid & 63) * 16;
            const uint4 a = *(const uint4*)qrow, b = *(const uint4*)(qrow + 1024);
            const uint2 c = *(const uint2*)(qrow + 2048);
            #define SQ(v) (bf_lo(v) * bf_lo(v) + bf_hi(v) * bf_hi(v))
            const float n = SQ(a.x) + SQ(a.y) + SQ(a.z) + SQ(a.w) + SQ(b.x) + SQ(b.y) + SQ(b.z) + SQ(b.w) + SQ(c.x) + SQ(c.y);
            qmax2 = max(qmax2, __float_as_uint(n) & 0x7FFFFFFFu);
            *(uint2*)(qrow + 2048 + 8) = make_uint2(0x3F803F80u, 0u);
        }
        asm volatile("fence.proxy.async.shared::cta;" ::: "memory");
        mbar_sleep(bar_kfull + 32, 0);
        bar_arrive(8, 512);
        uint32_t safe;
        {
            const float kmax2 = __uint_as_float(__reduce_max_sync(0xffffffffu, __float_as_uint(s_stat[lane])));
            const int ev = (int)(__reduce_max_sync(0xffffffffu, __float_as_uint(s_stat[32 + lane])) >> 23) - 126;
            const float bmax = fminf(100.f, fminf((float)(110 - max(ev, 1)), (float)(88 + ev)));
            const bool ok = bmax > 0.f && __uint_as_float(qmax2) * kmax2 <= bmax * bmax;
            asm volatile("{\n.reg .pred p, q;\nsetp.ne.u32 p, %1, 0;\nbarrier.red.and.pred.aligned q, %2, 128, p;\nselp.u32 %0, 1, 0, q;\n}"
                         : "=r"(safe) : "r"((uint32_t)ok), "r"(4 + wg) : "memory");
            safe = __shfl_sync(0xffffffffu, safe, 0);
            if (!safe) {
                #pragma unroll 1
                for (int i = p0 + (tid >> 6); i < 3; i += 2) *(uint2*)(sm + SM_Q + HEAD(i) * 3072 + (tid & 63) * 16 + 2048 + 8) = make_uint2(0u, 0u);
                asm volatile("fence.proxy.async.shared::cta;" ::: "memory");
                bar_sync(4 + wg, 128);
            }
        }
        const uint32_t kv16 = ((sb + SM_KV) & 0x3FFFFu) >> 4;
        constexpr uint32_t KLBO = 8u << 16, KHI = 24u, VLBO = (24u << 16) + 192u, VHI = 8u;
        const bool lead = lane == 0;
        const int r0 = 16 * w + g;
        static_assert(KST == 4, "ring phases below assume 4 stages");
        if (wg == 2) {
            bar_sync(14, 256);
            mbar_wait(bar_kfull + 24, 1);
        }
        const uint32_t q16 = ((sb + SM_Q) & 0x3FFFFu) >> 4;
        uint64_t qa = mkdesc(q16 + HEAD(p0) * 192 + (64u << 16), 8), qb = mkdesc(q16 + HEAD(p0) * 192 + 128 + ((uint32_t)(1536 - 128 - HEAD(p0) * 192) << 16), 8);
        #define NEXT_HEAD(ps) { const uint32_t d_ = (ps) == 0 ? 384 : 576; qa += d_; qb += (uint64_t)d_ - ((uint64_t)d_ << 16); }
        const uint64_t dk = mkdesc(kv16 + KLBO, KHI), dv = mkdesc(kv16 + VLBO, VHI);
        const uint32_t kep = bar_kempty + peer_off;
        uint32_t rc = lead ? (wg == 0 ? 2 : 1) : 0;
        float o[12];
        #pragma unroll
        for (int i = 0; i < 12; i++) o[i] = 0.f;
        float s[32]; uint32_t pa[16], pb[16];
        FENCE_F(o, 12);
        #define QK(off) wgmma_ss_n64<0, 0>(s, qa, dk + (off), 0); wgmma_ss_n64<0, 0>(s, qb, dk + (off) + 16, 1);
        #define PV(pp, off) wgmma_rs_n24<1>(o, pp[0], pp[1], pp[2], pp[3], dv + (off), 1); wgmma_rs_n24<1>(o, pp[4], pp[5], pp[6], pp[7], dv + (off) + 48, 1); \
                            wgmma_rs_n24<1>(o, pp[8], pp[9], pp[10], pp[11], dv + (off) + 96, 1); wgmma_rs_n24<1>(o, pp[12], pp[13], pp[14], pp[15], dv + (off) + 144, 1);
        #define STORE_O(h) { \
            const float l0 = __shfl_sync(0xffffffffu, o[8], (lane & ~3) | 2), l1 = __shfl_sync(0xffffffffu, o[10], (lane & ~3) | 2); \
            const float i0 = s_gate[r0] / l0, i1 = s_gate[r0 + 8] / l1; \
            _Pragma("unroll") for (int b = 0; b < 3; b++) { \
                if (b < 2 || t < 2) { \
                    const int cq = 20 * (h) + 8 * b + 2 * t, col = cq < 32 ? ct * 32 + cq : (cq < 96 ? 96 + ct * 64 + cq : 288 + ct * 64 + cq); \
                    uint8_t* dst = g_op + (size_t)((rb * 80 + (col >> 3)) * 8 + 2 * w) * 128 + g * 16 + (col & 7) * 2; \
                    *(uint32_t*)dst = pack_bf16(o[4 * b] * i0, o[4 * b + 1] * i0); \
                    *(uint32_t*)(dst + 128) = pack_bf16(o[4 * b + 2] * i1, o[4 * b + 3] * i1); \
                } \
            } \
            _Pragma("unroll") for (int i = 0; i < 12; i++) o[i] = 0.f; \
            FENCE_F(o, 12); \
            __syncwarp(); \
            TRACE(22 + (h)); }
        if (safe) {
            wg_fence();
            QK(3 * 768 + 384)
            wg_commit();
            TRACE(16 + wg);
            wg_wait<0>();
            FENCE_F(s, 32);
            release2n(bar_kempty + 24, kep + 24, rc);
            EXPBLK(pa, s);
            FENCE_R(pa, 16);
            #define HALF(off, pin, pout) \
                wg_fence(); \
                QK(off) \
                wg_commit(); \
                PV(pin, off) \
                wg_commit(); \
                wg_wait<1>(); \
                FENCE_F(s, 32); \
                EXPBLK(pout, s); \
                FENCE_R(pout, 16); \
                wg_wait<0>();
            #pragma unroll 1
            for (int J4 = 4 * p0; J4 < 12; J4++) {
                const uint32_t ph = J4 & 1;
                #pragma unroll
                for (int st = 0; st < 4; st++) {
                    mbar_wait(bar_kfull + 8 * st, ph);
                    if (st == 3 && J4 == 3 && wg == 0) bar_arrive(14, 256);
                    HALF(st * 768, pa, pb)
                    if (st == 3 && (J4 & 3) == 3 && J4 < 11) NEXT_HEAD(J4 >> 2)
                    HALF(st * 768 + 384, pb, pa)
                    if (st < 3) release2n(bar_kempty + 8 * st, kep + 8 * st, rc);
                }
                if ((J4 & 3) == 3) {
                    FENCE_F(o, 12);
                    STORE_O(HEAD(J4 >> 2))
                    rc = lead ? 1 : 0;
                }
                release2n(bar_kempty + 24, kep + 24, rc);
            }
        } else {
            float m0 = -INFINITY, m1 = -INFINITY;
            #pragma unroll 1
            for (int u = 32 * p0; u < 96; u++) {
                const int J = u >> 1;
                if ((u & 1) == 0) mbar_wait(bar_kfull + 8 * (J & 3), (J >> 2) & 1);
                if (u == 30 && wg == 0) bar_arrive(14, 256);
                wg_fence();
                QK(((u + 7) & 7) * 384)
                wg_commit();
                wg_wait<0>();
                FENCE_F(s, 32);
                float x0 = m0, x1 = m1;
                #pragma unroll
                for (int b = 0; b < 8; b++) {
                    const float f = ((PAT >> b) & 1) ? 0.5f : 1.f;
                    s[4 * b] *= f; s[4 * b + 1] *= f; s[4 * b + 2] *= f; s[4 * b + 3] *= f;
                    x0 = fmaxf(x0, fmaxf(s[4 * b], s[4 * b + 1])); x1 = fmaxf(x1, fmaxf(s[4 * b + 2], s[4 * b + 3]));
                }
                x0 = fmaxf(x0, __shfl_xor_sync(0xffffffffu, x0, 1)); x0 = fmaxf(x0, __shfl_xor_sync(0xffffffffu, x0, 2));
                x1 = fmaxf(x1, __shfl_xor_sync(0xffffffffu, x1, 1)); x1 = fmaxf(x1, __shfl_xor_sync(0xffffffffu, x1, 2));
                const float f0 = exp2f(m0 - x0), f1 = exp2f(m1 - x1);
                m0 = x0; m1 = x1;
                #pragma unroll
                for (int b = 0; b < 3; b++) { o[4 * b] *= f0; o[4 * b + 1] *= f0; o[4 * b + 2] *= f1; o[4 * b + 3] *= f1; }
                #pragma unroll
                for (int b = 0; b < 8; b++) {
                    pa[2 * b] = exp2_mufu(s[4 * b] - m0, s[4 * b + 1] - m0);
                    pa[2 * b + 1] = exp2_mufu(s[4 * b + 2] - m1, s[4 * b + 3] - m1);
                }
                FENCE_R(pa, 16); FENCE_F(o, 12);
                wg_fence();
                PV(pa, (u & 7) * 384)
                wg_commit();
                wg_wait<0>();
                FENCE_F(o, 12);
                if ((u & 1) == 0) release2n(bar_kempty + 8 * ((J + 3) & 3), kep + 8 * ((J + 3) & 3), rc);
                if ((u & 31) == 31) {
                    STORE_O(HEAD(u >> 5))
                    m0 = -INFINITY; m1 = -INFINITY;
                    NEXT_HEAD(u >> 5)
                    rc = lead ? 1 : 0;
                }
            }
        }
        bar_sync(4 + wg, 128);
        if (tid == 0) flag_add(F_O + rb * 3 + 2);
    }
}

typedef CUresult (*EncodeFn)(CUtensorMap*, CUtensorMapDataType, cuuint32_t, void*, const cuuint64_t*, const cuuint64_t*, const cuuint32_t*,
                             const cuuint32_t*, CUtensorMapInterleave, CUtensorMapSwizzle, CUtensorMapL2promotion, CUtensorMapFloatOOBfill);

void make_map(EncodeFn fn, CUtensorMap* m, const void* ptr, uint64_t cols, uint64_t rows, uint32_t bc, uint32_t br, CUtensorMapSwizzle sw) {
    cuuint64_t dims[2] = {cols, rows}, strides[1] = {cols * 2};
    cuuint32_t box[2] = {bc, br}, es[2] = {1, 1};
    fn(m, CU_TENSOR_MAP_DATA_TYPE_BFLOAT16, 2, const_cast<void*>(ptr), dims, strides, box, es, CU_TENSOR_MAP_INTERLEAVE_NONE, sw,
       CU_TENSOR_MAP_L2_PROMOTION_L2_128B, CU_TENSOR_MAP_FLOAT_OOB_FILL_NONE);
}

void make_map3(EncodeFn fn, CUtensorMap* m, const void* ptr, uint64_t cols, uint64_t rows, uint32_t natoms) {
    cuuint64_t dims[3] = {32, rows, cols / 32}, strides[2] = {cols * 2, 64};
    cuuint32_t box[3] = {32, 32, natoms}, es[3] = {1, 1, 1};
    fn(m, CU_TENSOR_MAP_DATA_TYPE_BFLOAT16, 3, const_cast<void*>(ptr), dims, strides, box, es, CU_TENSOR_MAP_INTERLEAVE_NONE, CU_TENSOR_MAP_SWIZZLE_64B,
       CU_TENSOR_MAP_L2_PROMOTION_L2_128B, CU_TENSOR_MAP_FLOAT_OOB_FILL_NONE);
}

}

extern "C" void kernel_launch(void* const* d_in, const int* in_sizes, int n_in, void* d_out, int out_size) {
    static EncodeFn fn = nullptr;
    if (!fn) {
        cudaDriverEntryPointQueryResult qr;
        void* f = nullptr;
        cudaGetDriverEntryPoint("cuTensorMapEncodeTiled", &f, cudaEnableDefault, &qr);
        fn = (EncodeFn)f;
        cudaFuncSetAttribute(mega_kernel, cudaFuncAttributeMaxDynamicSharedMemorySize, SM_TOTAL);
    }
    Params p;
    const __nv_bfloat16* x = (const __nv_bfloat16*)d_in[0];
    make_map(fn, &p.mx, x, DM, S_LEN, 64, 64, CU_TENSOR_MAP_SWIZZLE_128B);
    make_map(fn, &p.mwsp, d_in[7], S_LEN, S_LEN, 64, 64, CU_TENSOR_MAP_SWIZZLE_128B);
    make_map3(fn, &p.mwq, d_in[1], DM, DM, 5);
    make_map3(fn, &p.mwin, d_in[6], 2 * FH, DM, 7);
    p.x = x;
    p.wq = (const __nv_bfloat16*)d_in[1];
    p.win = (const __nv_bfloat16*)d_in[6];
    p.wk = (const __nv_bfloat16*)d_in[2];
    p.wv = (const __nv_bfloat16*)d_in[3];
    p.bsp = (const __nv_bfloat16*)d_in[8];
    p.gw = (const __nv_bfloat16*)d_in[10];
    p.wsp = (const __nv_bfloat16*)d_in[7];
    p.wo = (const __nv_bfloat16*)d_in[4];
    p.wout = (const __nv_bfloat16*)d_in[9];
    p.out = (__nv_bfloat16*)d_out;
    mega_kernel<<<NCTA, 640, SM_TOTAL>>>(p);
}
```

```cpp
#include <cuda_runtime.h>
#include <cuda_bf16.h>
#include <cuda.h>
#include <stdint.h>

namespace {

constexpr int S_LEN = 2048, DM = 640, FH = 864;
constexpr int NCTA = 128;
#define PAT8 0xB5u
constexpr uint32_t PAT = PAT8 * 0x101u;
#define GB2 0
#define GB3 -1
#define GB4 2
#define GB5 -1
constexpr int GST = 4;
constexpr int GST_BYTES = 36864;
constexpr int KST = 4;
constexpr int KST_BYTES = 12288;
constexpr int QS_PITCH = 168;
constexpr int SM_G = 0;
constexpr int SM_KV = SM_G + GST * GST_BYTES;
constexpr int SM_Q = SM_KV + KST * KST_BYTES;
constexpr int SM_MISC = SM_Q + 8 * 3072 + 1024;
constexpr int SM_W = SM_G + 2 * GST_BYTES + 16384;
constexpr int SM_TOTAL = SM_MISC + 2048 + 1024;

constexpr int F_KV = 0, F_DONE = 1, F_W2 = 2, F_WR = 3, F_W1 = 4, F_STAT = 5, F_Z2 = F_STAT + 32, F_H = F_Z2 + 128, F_O = F_H + 32, F_NUM = F_O + 96;

__device__ __align__(1024) uint8_t g_kv[16 * KST_BYTES];
__device__ __align__(1024) uint8_t g_z2n[4 * 32 * 28672];
__device__ __align__(1024) uint8_t g_hp[32 * 108 * 1024];
__device__ __align__(1024) uint8_t g_op[32 * 80 * 1024];
__device__ __align__(1024) uint8_t g_wot[4 * 80 * 2560];
__device__ __align__(1024) uint8_t g_woutt[4 * 108 * 2560];
__device__ __align__(1024) uint4 g_z1[2 * NCTA * 14 * 128];
__device__ uint4 g_part[32 * 4 * 64];
__device__ __align__(128) float g_kvmax[64];
__device__ __align__(128) float g_gate[S_LEN];
__device__ unsigned g_flags[F_NUM * 8];
__device__ uint32_t g_const[4] = {0u, 0u, 0x3F003F00u, 0u};

struct Params {
    CUtensorMap mx, mwsp, mwq, mwin;
    const __nv_bfloat16 *x, *wk, *wv, *bsp, *gw, *wsp, *wo, *wout, *wq, *win;
    __nv_bfloat16* out;
};

template<int TB> __device__ __forceinline__ void wgmma_rs_n24(float (&d)[12], uint32_t a0, uint32_t a1, uint32_t a2, uint32_t a3, uint64_t db, int scale_d) {
  asm volatile("{\n.reg .pred p;\nsetp.ne.b32 p, %17, 0;\nwgmma.mma_async.sync.aligned.m64n24k16.f32.bf16.bf16 {%0,%1,%2,%3,%4,%5,%6,%7,%8,%9,%10,%11}, {%12,%13,%14,%15}, %16, p, 1, 1, %18;\n}"
    : "+f"(d[0]), "+f"(d[1]), "+f"(d[2]), "+f"(d[3]), "+f"(d[4]), "+f"(d[5]), "+f"(d[6]), "+f"(d[7]), "+f"(d[8]), "+f"(d[9]), "+f"(d[10]), "+f"(d[11])
    : "r"(a0), "r"(a1), "r"(a2), "r"(a3), "l"(db), "r"(scale_d), "n"(TB));
}
template<int TA, int TB> __device__ __forceinline__ void wgmma_ss_n48(float (&d)[24], uint64_t da, uint64_t db, int scale_d) {
  asm volatile("{\n.reg .pred p;\nsetp.ne.b32 p, %26, 0;\nwgmma.mma_async.sync.aligned.m64n48k16.f32.bf16.bf16 {%0,%1,%2,%3,%4,%5,%6,%7,%8,%9,%10,%11,%12,%13,%14,%15,%16,%17,%18,%19,%20,%21,%22,%23}, %24, %25, p, 1, 1, %27, %28;\n}"
    : "+f"(d[0]), "+f"(d[1]), "+f"(d[2]), "+f"(d[3]), "+f"(d[4]), "+f"(d[5]), "+f"(d[6]), "+f"(d[7]), "+f"(d[8]), "+f"(d[9]), "+f"(d[10]), "+f"(d[11]), "+f"(d[12]), "+f"(d[13]), "+f"(d[14]), "+f"(d[15]), "+f"(d[16]), "+f"(d[17]), "+f"(d[18]), "+f"(d[19]), "+f"(d[20]), "+f"(d[21]), "+f"(d[22]), "+f"(d[23])
    : "l"(da), "l"(db), "r"(scale_d), "n"(TA), "n"(TB));
}
template<int TA, int TB> __device__ __forceinline__ void wgmma_ss_n64(float (&d)[32], uint64_t da, uint64_t db, int scale_d) {
  asm volatile("{\n.reg .pred p;\nsetp.ne.b32 p, %34, 0;\nwgmma.mma_async.sync.aligned.m64n64k16.f32.bf16.bf16 {%0,%1,%2,%3,%4,%5,%6,%7,%8,%9,%10,%11,%12,%13,%14,%15,%16,%17,%18,%19,%20,%21,%22,%23,%24,%25,%26,%27,%28,%29,%30,%31}, %32, %33, p, 1, 1, %35, %36;\n}"
    : "+f"(d[0]), "+f"(d[1]), "+f"(d[2]), "+f"(d[3]), "+f"(d[4]), "+f"(d[5]), "+f"(d[6]), "+f"(d[7]), "+f"(d[8]), "+f"(d[9]), "+f"(d[10]), "+f"(d[11]), "+f"(d[12]), "+f"(d[13]), "+f"(d[14]), "+f"(d[15]), "+f"(d[16]), "+f"(d[17]), "+f"(d[18]), "+f"(d[19]), "+f"(d[20]), "+f"(d[21]), "+f"(d[22]), "+f"(d[23]), "+f"(d[24]), "+f"(d[25]), "+f"(d[26]), "+f"(d[27]), "+f"(d[28]), "+f"(d[29]), "+f"(d[30]), "+f"(d[31])
    : "l"(da), "l"(db), "r"(scale_d), "n"(TA), "n"(TB));
}
template<int TA, int TB> __device__ __forceinline__ void wgmma_ss_n96(float (&d)[48], uint64_t da, uint64_t db, int scale_d) {
  asm volatile("{\n.reg .pred p;\nsetp.ne.b32 p, %50, 0;\nwgmma.mma_async.sync.aligned.m64n96k16.f32.bf16.bf16 {%0,%1,%2,%3,%4,%5,%6,%7,%8,%9,%10,%11,%12,%13,%14,%15,%16,%17,%18,%19,%20,%21,%22,%23,%24,%25,%26,%27,%28,%29,%30,%31,%32,%33,%34,%35,%36,%37,%38,%39,%40,%41,%42,%43,%44,%45,%46,%47}, %48, %49, p, 1, 1, %51, %52;\n}"
    : "+f"(d[0]), "+f"(d[1]), "+f"(d[2]), "+f"(d[3]), "+f"(d[4]), "+f"(d[5]), "+f"(d[6]), "+f"(d[7]), "+f"(d[8]), "+f"(d[9]), "+f"(d[10]), "+f"(d[11]), "+f"(d[12]), "+f"(d[13]), "+f"(d[14]), "+f"(d[15]), "+f"(d[16]), "+f"(d[17]), "+f"(d[18]), "+f"(d[19]), "+f"(d[20]), "+f"(d[21]), "+f"(d[22]), "+f"(d[23]), "+f"(d[24]), "+f"(d[25]), "+f"(d[26]), "+f"(d[27]), "+f"(d[28]), "+f"(d[29]), "+f"(d[30]), "+f"(d[31]), "+f"(d[32]), "+f"(d[33]), "+f"(d[34]), "+f"(d[35]), "+f"(d[36]), "+f"(d[37]), "+f"(d[38]), "+f"(d[39]), "+f"(d[40]), "+f"(d[41]), "+f"(d[42]), "+f"(d[43]), "+f"(d[44]), "+f"(d[45]), "+f"(d[46]), "+f"(d[47])
    : "l"(da), "l"(db), "r"(scale_d), "n"(TA), "n"(TB));
}
template<int TA, int TB> __device__ __forceinline__ void wgmma_ss_n128(float (&d)[64], uint64_t da, uint64_t db, int scale_d) {
  asm volatile("{\n.reg .pred p;\nsetp.ne.b32 p, %66, 0;\nwgmma.mma_async.sync.aligned.m64n128k16.f32.bf16.bf16 {%0,%1,%2,%3,%4,%5,%6,%7,%8,%9,%10,%11,%12,%13,%14,%15,%16,%17,%18,%19,%20,%21,%22,%23,%24,%25,%26,%27,%28,%29,%30,%31,%32,%33,%34,%35,%36,%37,%38,%39,%40,%41,%42,%43,%44,%45,%46,%47,%48,%49,%50,%51,%52,%53,%54,%55,%56,%57,%58,%59,%60,%61,%62,%63}, %64, %65, p, 1, 1, %67, %68;\n}"
    : "+f"(d[0]), "+f"(d[1]), "+f"(d[2]), "+f"(d[3]), "+f"(d[4]), "+f"(d[5]), "+f"(d[6]), "+f"(d[7]), "+f"(d[8]), "+f"(d[9]), "+f"(d[10]), "+f"(d[11]), "+f"(d[12]), "+f"(d[13]), "+f"(d[14]), "+f"(d[15]), "+f"(d[16]), "+f"(d[17]), "+f"(d[18]), "+f"(d[19]), "+f"(d[20]), "+f"(d[21]), "+f"(d[22]), "+f"(d[23]), "+f"(d[24]), "+f"(d[25]), "+f"(d[26]), "+f"(d[27]), "+f"(d[28]), "+f"(d[29]), "+f"(d[30]), "+f"(d[31]), "+f"(d[32]), "+f"(d[33]), "+f"(d[34]), "+f"(d[35]), "+f"(d[36]), "+f"(d[37]), "+f"(d[38]), "+f"(d[39]), "+f"(d[40]), "+f"(d[41]), "+f"(d[42]), "+f"(d[43]), "+f"(d[44]), "+f"(d[45]), "+f"(d[46]), "+f"(d[47]), "+f"(d[48]), "+f"(d[49]), "+f"(d[50]), "+f"(d[51]), "+f"(d[52]), "+f"(d[53]), "+f"(d[54]), "+f"(d[55]), "+f"(d[56]), "+f"(d[57]), "+f"(d[58]), "+f"(d[59]), "+f"(d[60]), "+f"(d[61]), "+f"(d[62]), "+f"(d[63])
    : "l"(da), "l"(db), "r"(scale_d), "n"(TA), "n"(TB));
}

__device__ __forceinline__ uint64_t mkdesc(uint32_t lo, uint32_t hi) { uint64_t d; asm("mov.b64 %0, {%1, %2};" : "=l"(d) : "r"(lo), "r"(hi)); return d; }
__device__ __forceinline__ void mbar_init(uint32_t a, int c) { asm volatile("mbarrier.init.shared::cta.b64 [%0], %1;" :: "r"(a), "r"(c)); }
__device__ __forceinline__ void mbar_expect(uint32_t a, uint32_t b) { asm volatile("mbarrier.arrive.expect_tx.shared::cta.b64 _, [%0], %1;" :: "r"(a), "r"(b) : "memory"); }
__device__ __forceinline__ void mbar_arrive(uint32_t a) { asm volatile("mbarrier.arrive.shared::cta.b64 _, [%0];" :: "r"(a) : "memory"); }
#define TRACE(i)
#define TRW(i)
#define TR2(k, i)
#define SPIN_LIMIT (1 << 20)
#define SPIN_FAIL(code) __trap()
__device__ __forceinline__ void mbar_wait(uint32_t a, uint32_t ph) {
    asm volatile("{\n.reg .pred p, q;\n.reg .u32 c;\nmov.u32 c, 0;\n"
                 "W0:\nmbarrier.try_wait.parity.shared::cta.b64 p, [%0], %1;\n@p bra W1;\n"
                 "add.u32 c, c, 1;\nsetp.lt.u32 q, c, %2;\n@q bra W0;\ntrap;\n"
                 "W1:\n}" :: "r"(a), "r"(ph), "n"(4 * SPIN_LIMIT) : "memory");
}
__device__ __forceinline__ void mbar_sleep(uint32_t a, uint32_t ph) {
    asm volatile("{\n.reg .pred p, q;\n.reg .u32 c;\nmov.u32 c, 0;\n"
                 "W0:\nmbarrier.try_wait.parity.shared::cta.b64 p, [%0], %1, 4000;\n@p bra W1;\n"
                 "add.u32 c, c, 1;\nsetp.lt.u32 q, c, %2;\n@q bra W0;\ntrap;\n"
                 "W1:\n}" :: "r"(a), "r"(ph), "n"(SPIN_LIMIT) : "memory");
}
__device__ __forceinline__ uint32_t mbar_try(uint32_t a, uint32_t ph) {
    uint32_t ok;
    asm volatile("{\n.reg .pred p;\nmbarrier.test_wait.parity.shared::cta.b64 p, [%1], %2;\nselp.u32 %0, 1, 0, p;\n}" : "=r"(ok) : "r"(a), "r"(ph) : "memory");
    return ok;
}
__device__ __forceinline__ void wg_fence() { asm volatile("wgmma.fence.sync.aligned;" ::: "memory"); }
__device__ __forceinline__ void wg_commit() { asm volatile("wgmma.commit_group.sync.aligned;" ::: "memory"); }
template<int N> __device__ __forceinline__ void wg_wait() { asm volatile("wgmma.wait_group.sync.aligned %0;" :: "n"(N) : "memory"); }
__device__ __forceinline__ void bar_sync(int id, int n) { asm volatile("bar.sync %0, %1;" :: "r"(id), "r"(n) : "memory"); }
__device__ __forceinline__ void bar_arrive(int id, int n) { asm volatile("bar.arrive %0, %1;" :: "r"(id), "r"(n) : "memory"); }
__device__ __forceinline__ void fence_async() { asm volatile("fence.proxy.async.global;" ::: "memory"); }
__device__ __forceinline__ void flag_wait(int f, unsigned target) {
    const unsigned* p = &g_flags[f * 8];
    unsigned v;
    #pragma unroll 1
    for (int it = 0; it < SPIN_LIMIT; it++) {
        asm volatile("ld.acquire.gpu.global.u32 %0, [%1];" : "=r"(v) : "l"(p) : "memory");
        if (v >= target) return;
        __nanosleep(20);
    }
    SPIN_FAIL(f);
}
__device__ __forceinline__ void flag_add(int f) { asm volatile("red.release.gpu.global.add.u32 [%0], 1;" :: "l"(&g_flags[f * 8]) : "memory"); }
__device__ __forceinline__ void tma2d(uint32_t dst, const CUtensorMap* m, int c0, int c1, uint32_t bar) {
    asm volatile("cp.async.bulk.tensor.2d.shared::cluster.global.mbarrier::complete_tx::bytes [%0], [%1, {%3, %4}], [%2];"
        :: "r"(dst), "l"(m), "r"(bar), "r"(c0), "r"(c1) : "memory");
}
__device__ __forceinline__ void bulk_ld(uint32_t dst, const void* src, uint32_t bytes, uint32_t bar) {
    asm volatile("cp.async.bulk.shared::cluster.global.mbarrier::complete_tx::bytes [%0], [%1], %2, [%3];"
        :: "r"(dst), "l"(src), "r"(bytes), "r"(bar) : "memory");
}
__device__ __forceinline__ void tma3d_mc(uint32_t dst, const CUtensorMap* m, int c1, int c2, uint32_t bar) {
    asm volatile("cp.async.bulk.tensor.3d.shared::cluster.global.mbarrier::complete_tx::bytes.multicast::cluster [%0], [%1, {0, %3, %4}], [%2], %5;"
        :: "r"(dst), "l"(m), "r"(bar), "r"(c1), "r"(c2), "h"((uint16_t)3) : "memory");
}
__device__ __forceinline__ void bulk_ld_mc(uint32_t dst, const void* src, uint32_t bytes, uint32_t bar) {
    asm volatile("cp.async.bulk.shared::cluster.global.mbarrier::complete_tx::bytes.multicast::cluster [%0], [%1], %2, [%3], %4;"
        :: "r"(dst), "l"(src), "r"(bytes), "r"(bar), "h"((uint16_t)3) : "memory");
}
__device__ __forceinline__ void release2(uint32_t a, uint32_t peer_off) {
    asm volatile("mbarrier.arrive.shared::cta.b64 _, [%0];\nmbarrier.arrive.shared::cluster.b64 _, [%1];" :: "r"(a), "r"(a + peer_off) : "memory");
}
__device__ __forceinline__ void release2n(uint32_t a, uint32_t pa, uint32_t cnt) {
    asm volatile("{\n.reg .pred p;\nsetp.ne.u32 p, %2, 0;\n@p mbarrier.arrive.shared::cta.b64 _, [%0], %2;\n@p mbarrier.arrive.shared::cluster.b64 _, [%1], %2;\n}"
                 :: "r"(a), "r"(pa), "r"(cnt) : "memory");
}
__device__ __forceinline__ bool elect_one() {
    uint32_t p;
    asm volatile("{\n.reg .pred q;\nelect.sync _|q, 0xffffffff;\nselp.u32 %0, 1, 0, q;\n}" : "=r"(p));
    return p != 0;
}
__device__ __forceinline__ void cluster_sync() { asm volatile("barrier.cluster.arrive.release;\nbarrier.cluster.wait.acquire;" ::: "memory"); }
__device__ __forceinline__ void l2_prefetch(const void* src, uint32_t bytes) {
    asm volatile("cp.async.bulk.prefetch.L2.global [%0], %1;" :: "l"(src), "r"(bytes) : "memory");
}
__device__ __forceinline__ uint32_t pack_bf16(float lo, float hi) { uint32_t r; asm("cvt.rn.bf16x2.f32 %0, %1, %2;" : "=r"(r) : "f"(hi), "f"(lo)); return r; }
__device__ __forceinline__ float bf_lo(uint32_t v) { return __uint_as_float(v << 16); }
__device__ __forceinline__ float bf_hi(uint32_t v) { return __uint_as_float(v & 0xFFFF0000u); }
__device__ __forceinline__ float gelu2_tanh(float x) {
    float u = x * fmaf(x * x, 0.0356774081363001f, 0.7978845608028654f), t;
    asm("tanh.approx.f32 %0, %1;" : "=f"(t) : "f"(u));
    return fmaf(x, t, x);
}
#define FENCE_F(a, n) _Pragma("unroll") for (int i_ = 0; i_ < n; i_++) asm volatile("" : "+f"(a[i_]) :: "memory");
#define FENCE_R(a, n) _Pragma("unroll") for (int i_ = 0; i_ < n; i_++) asm volatile("" : "+r"(a[i_]) :: "memory");

__device__ __forceinline__ uint32_t exp2_mufu(float a, float b) {
    float x, y;
    asm("ex2.approx.ftz.f32 %0, %1;" : "=f"(x) : "f"(a));
    asm("ex2.approx.ftz.f32 %0, %1;" : "=f"(y) : "f"(b));
    return pack_bf16(x, y);
}
__device__ __forceinline__ uint32_t exp2_alu(float a, float b, uint32_t half2c) {
    uint32_t L = __byte_perm(__float_as_uint(a), __float_as_uint(b), 0x6521), G, r;
    asm("lop3.b32 %0, %1, 0x007F007F, %2, 0xEA;" : "=r"(G) : "r"(L), "r"(half2c));
    uint32_t E = L & 0xFF80FF80u;
    asm("fma.rn.bf16x2 %0, %1, %2, %3;" : "=r"(r) : "r"(G), "r"(L), "r"(E));
    return r;
}
#define EXPBLK(p, s) _Pragma("unroll") for (int b = 0; b < 8; b++) { \
    if ((PAT >> b) & 1) { p[2*b] = exp2_alu(s[4*b], s[4*b+1], half2c); p[2*b+1] = exp2_alu(s[4*b+2], s[4*b+3], half2c); } \
    else { p[2*b] = exp2_mufu(s[4*b], s[4*b+1]); p[2*b+1] = exp2_mufu(s[4*b+2], s[4*b+3]); } }

struct Ring { uint32_t st, ph; };
template<int NST> __device__ __forceinline__ void ring_next(Ring& r) { if (++r.st == NST) { r.st = 0; r.ph ^= 1; } }

struct OpDesc { uint32_t lo, hi, step, step2, nsplit; };

template<int N, int PART> __device__ __forceinline__ void wgmma_ss(float (&d)[N / 2], uint64_t da, uint64_t db, int sc) {
    if constexpr (N == 160) {
        if constexpr (PART == 0) wgmma_ss_n96<0, 1>(*(float(*)[48])&d[0], da, db, sc);
        else wgmma_ss_n64<0, 1>(*(float(*)[32])&d[48], da, db, sc);
    } else if constexpr (N == 192) {
        if constexpr (PART == 0) wgmma_ss_n128<0, 1>(*(float(*)[64])&d[0], da, db, sc);
        else wgmma_ss_n64<0, 1>(*(float(*)[32])&d[64], da, db, sc);
    } else {
        if constexpr (PART == 0) wgmma_ss_n128<0, 1>(*(float(*)[64])&d[0], da, db, sc);
        else wgmma_ss_n96<0, 1>(*(float(*)[48])&d[64], da, db, sc);
    }
}

struct GemmCtx { Ring r; uint32_t sb16, bar_full, bar_empty, peer_off; bool lead; };

template<int N, int NS, int GB>
__device__ __forceinline__ void gemm_loop(float (&acc)[N / 2], int nkb, int first, OpDesc a, OpDesc b, GemmCtx& c) {
    uint32_t prev = 0;
    #pragma unroll 1
    for (int kb = 0; kb < nkb; kb++) {
        mbar_sleep(c.bar_full + 8 * c.r.st, c.r.ph);
        const uint32_t base = c.sb16 + c.r.st * (GST_BYTES / 16);
        const uint64_t da0 = mkdesc(base + a.lo, a.hi), db0 = mkdesc(base + b.lo, b.hi);
        wg_fence();
        #pragma unroll
        for (int k = 0; k < NS; k++) {
            const uint64_t da = da0 + k * a.step, db = db0 + ((k & 1) * b.step + (k >> 1) * b.step2);
            const int sc = (k > 0) | (kb > 0) | !first;
            wgmma_ss<N, 0>(acc, da, db, sc);
            if constexpr (GB > 0) { wg_commit(); wg_wait<GB - 1>(); }
            wgmma_ss<N, 1>(acc, da, db + b.nsplit, sc);
            if constexpr (GB < 0) {
                if ((k + 1) % (-GB) == 0 || k == NS - 1) {
                    wg_commit(); wg_wait<1>();
                    if (k < -GB && kb > 0 && c.lead) release2(c.bar_empty + 8 * prev, c.peer_off);
                }
            }
            if constexpr (GB > 0) {
                wg_commit(); wg_wait<GB - 1>();
                if (k == (GB - 1) / 2 && kb > 0 && c.lead) release2(c.bar_empty + 8 * prev, c.peer_off);
            }
        }
        if constexpr (GB == 0) {
            wg_commit();
            wg_wait<1>();
            if (kb > 0 && c.lead) release2(c.bar_empty + 8 * prev, c.peer_off);
        }
        prev = c.r.st;
        ring_next<GST>(c.r);
    }
    wg_wait<0>();
    if (c.lead) release2(c.bar_empty + 8 * prev, c.peer_off);
    FENCE_F(acc, N / 2);
}

template<int CNT, int SUBS>
__device__ __forceinline__ void retile_ld(uint4 (&v)[CNT], const __nv_bfloat16* src, int pitch, int ncg, int nkg, int cm0, int cnt, int id) {
    const int sub = id >> 3, row = id & 7;
    #pragma unroll
    for (int i = 0; i < CNT; i++) {
        const int l = sub + i * SUBS, cm = cm0 + l, kg = cm / ncg, cg = cm - kg * ncg;
        if (l < cnt && kg < nkg) v[i] = __ldg((const uint4*)(src + (size_t)(kg * 8 + row) * pitch + cg * 8));
    }
}
template<int NG, int CNT, int SUBS, bool PERM>
__device__ __forceinline__ void retile_st(const uint4 (&v)[CNT], int ncg, int nkg, uint8_t* dst, int cm0, int cnt, int id) {
    const int sub = id >> 3, row = id & 7;
    #pragma unroll
    for (int i = 0; i < CNT; i++) {
        const int l = sub + i * SUBS, cm = cm0 + l, kg = cm / ncg, cg = cm - kg * ncg, tile = cg / NG;
        int kd = kg;
        if (PERM) { const int q = kg / 20, rem = kg - q * 20; kd = rem < 4 ? q * 4 + rem : (rem < 12 ? 12 + q * 8 + rem : 36 + q * 8 + rem); }
        if (l < cnt && kg < nkg) *(uint4*)(dst + (size_t)((tile * nkg + kd) * NG + (cg - tile * NG)) * 128 + row * 16) = v[i];
    }
}

__global__ void __cluster_dims__(2, 1, 1) __launch_bounds__(640, 1) mega_kernel(const __grid_constant__ Params p) {
    extern __shared__ uint8_t smem_raw[];
    if (threadIdx.x == 0) TRW(31);
    const uint32_t sb = ((uint32_t)__cvta_generic_to_shared(smem_raw) + 1023u) & ~1023u;
    uint8_t* sm = smem_raw + (sb - (uint32_t)__cvta_generic_to_shared(smem_raw));
    const uint32_t bar_gfull = sb + SM_MISC, bar_gempty = bar_gfull + 64, bar_kfull = bar_gfull + 128, bar_kempty = bar_gfull + 192;
    float* s_gate = (float*)(sm + SM_MISC + 256);
    float* s_stat = (float*)(sm + SM_MISC + 512);
    float* s_red = (float*)(sm + SM_MISC + 768);
    float* s_ln = (float*)(sm + SM_MISC + 1024);
    const int rb = blockIdx.x & 31, ct = blockIdx.x >> 5;
    const int rank = rb & 1;
    const int wg = __shfl_sync(0xffffffffu, threadIdx.x >> 7, 0);
    const int tid = threadIdx.x & 127, w = tid >> 5, lane = tid & 31, g = lane >> 2, t = lane & 3;
    uint32_t peer_off;
    asm("mapa.shared::cluster.u32 %0, %1, %2;" : "=r"(peer_off) : "r"(sb), "r"(rank ^ 1));
    peer_off -= sb;

    if (threadIdx.x == 544) {
        l2_prefetch(p.wq + (size_t)blockIdx.x * 3200, 6400);
        l2_prefetch(p.win + (size_t)blockIdx.x * 8640, 17280);
    }
    if (__shfl_sync(0xffffffffu, threadIdx.x >> 5, 0) == 16 && elect_one()) {
        for (int i = 0; i < GST; i++) { mbar_init(bar_gfull + 8 * i, 1); mbar_init(bar_gempty + 8 * i, 8); }
        for (int i = 0; i < KST; i++) { mbar_init(bar_kfull + 8 * i, 1); mbar_init(bar_kempty + 8 * i, 24); }
        mbar_init(bar_kfull + 32, 1); mbar_init(bar_kfull + 40, 1); mbar_init(bar_kfull + 48, 1);
        asm volatile("fence.mbarrier_init.release.cluster;" ::: "memory");
        asm volatile("fence.proxy.async.shared::cta;" ::: "memory");
        if (ct == 3) {
            mbar_arrive(bar_gfull + 24);
            mbar_expect(bar_kfull + 48, 2 * 25600 + 1280);
            bulk_ld(sb + SM_W, p.wk, 25600, bar_kfull + 48);
            bulk_ld(sb + SM_W + 25600, p.wv, 25600, bar_kfull + 48);
            bulk_ld(sb + SM_W + 51200, p.gw, 1280, bar_kfull + 48);
            #pragma unroll 1
            for (int kb = 0; kb < 10; kb++) {
                if ((kb & 3) == 0) mbar_expect(bar_gfull + (kb >> 2) * 8, kb < 8 ? 32768 : 16384);
                tma2d(sb + SM_G + (kb >> 2) * GST_BYTES + (kb & 3) * 8192, &p.mx, kb * 64, rb * 64, bar_gfull + (kb >> 2) * 8);
            }
        }
    }
    asm volatile("barrier.cluster.arrive.relaxed;\nbarrier.cluster.wait.acquire;" ::: "memory");

    if (wg == 4) {
        asm volatile("setmaxnreg.dec.sync.aligned.u32 24;");
        const int wu = __shfl_sync(0xffffffffu, w, 0);
        static_assert(GST == 4, "ring indices are derived from a running stage counter");
        #define STG_ADDR(n) (sb + SM_G + ((n) & 3) * GST_BYTES)
        #define STG_FULL(n) (bar_gfull + ((n) & 3) * 8)
        #define STG_WAIT(n) mbar_sleep(bar_gempty + ((n) & 3) * 8, (((n) >> 2) & 1) ^ 1)
        const uint32_t n0 = ct == 3 ? 4 : 0;
        if (wu == 0) {
            uint32_t n = n0;
            if (elect_one()) {
                #pragma unroll 1
                for (int kb = 0; kb < 10; kb++, n++) {
                    STG_WAIT(n);
                    mbar_expect(STG_FULL(n), 8192 + 20480);
                    tma3d_mc(STG_ADDR(n) + 8192 + rank * 10240, &p.mwq, kb * 64 + rank * 32, 5 * ct, STG_FULL(n));
                }
                #pragma unroll 1
                for (int i = 0; i < 20; i++, n++) {
                    STG_WAIT(n);
                    mbar_expect(STG_FULL(n), 8192 + 28672);
                    tma3d_mc(STG_ADDR(n) + 8192 + rank * 14336, &p.mwin, (i < 10 ? i : i - 10) * 64 + rank * 32, (i < 10 ? 27 : 0) + 7 * ct, STG_FULL(n));
                }
            }
            __syncwarp();
            #pragma unroll 1
            for (int it = 0; ; it++) {
                unsigned v;
                asm volatile("ld.acquire.gpu.global.u32 %0, [%1];" : "=r"(v) : "l"(&g_flags[(F_Z2 + lane * 4 + ct) * 8]) : "memory");
                if (__all_sync(0xffffffffu, v != 0)) break;
                if (it > SPIN_LIMIT) SPIN_FAIL(F_Z2);
                __nanosleep(20);
            }
            if (elect_one()) {
                n = n0 + 30;
                fence_async();
                const uint8_t* src = g_z2n + (size_t)ct * 32 * 28672 + rank * 14336;
                #pragma unroll 1
                for (int kb = 0; kb < 32; kb++, n++, src += 28672) {
                    STG_WAIT(n);
                    mbar_expect(STG_FULL(n), 8192 + 28672);
                    bulk_ld_mc(STG_ADDR(n) + 8192 + rank * 14336, src, 14336, STG_FULL(n));
                }
                flag_wait(F_WR, 96);
                fence_async();
                n++;
                #pragma unroll 1
                for (int i = 0; i < 2; i++, n++) {
                    STG_WAIT(n);
                    mbar_expect(STG_FULL(n), 28672);
                    bulk_ld_mc(STG_ADDR(n) + 8192 + rank * 10240, g_wot + (size_t)(ct * 80 + i * 8) * 2560 + rank * 10240, 10240, STG_FULL(n));
                }
                uint32_t k0 = 28 * ct + rank * 4;
                #pragma unroll 1
                for (int i = 0; i < 14; i++, n++) {
                    const uint32_t nk = i == 13 ? 2 : 4;
                    if (i == 13) k0 -= rank * 2;
                    if (k0 >= 108) k0 -= 108;
                    STG_WAIT(n);
                    mbar_expect(STG_FULL(n), nk * 2 * (2560 + 1024));
                    bulk_ld_mc(STG_ADDR(n) + 8192 + rank * nk * 2560, g_woutt + (size_t)(ct * 108 + k0) * 2560, nk * 2560, STG_FULL(n));
                    k0 += 8;
                }
                #pragma unroll 1
                for (int i = 2; i < 10; i++, n++) {
                    STG_WAIT(n);
                    mbar_expect(STG_FULL(n), 28672);
                    bulk_ld_mc(STG_ADDR(n) + 8192 + rank * 10240, g_wot + (size_t)(ct * 80 + i * 8) * 2560 + rank * 10240, 10240, STG_FULL(n));
                }
            }
        } else if (wu == 3) {
            if (elect_one()) {
                uint32_t n = n0;
                #pragma unroll 1
                for (int j = 0; j < 3; j++) {
                    #pragma unroll 1
                    for (int kb = 0; kb < 10; kb++, n++) {
                        STG_WAIT(n);
                        tma2d(STG_ADDR(n), &p.mx, kb * 64, rb * 64, STG_FULL(n));
                        if (j > 0 && kb >= 2) l2_prefetch(p.wsp + (size_t)(rb * 64 + ct * 16 + (j - 1) * 8 + kb - 2) * S_LEN, 4096);
                    }
                }
                #define STASH_STAGE(which) { STG_WAIT(n); fence_async(); mbar_expect(STG_FULL(n), 28672); \
                    bulk_ld(STG_ADDR(n), g_z1 + (size_t)((which) * NCTA + blockIdx.x) * 1792, 28672, STG_FULL(n)); n++; }
                #pragma unroll 1
                for (int kb = 0; kb < 32; kb++, n++) {
                    STG_WAIT(n);
                    tma2d(STG_ADDR(n), &p.mwsp, kb * 64, rb * 64, STG_FULL(n));
                }
                STASH_STAGE(0)
                const uint8_t* op = g_op + (size_t)rb * 80 * 1024;
                const uint8_t* hp = g_hp + (size_t)rb * 108 * 1024;
                flag_wait(F_O + rb * 3, 4);
                fence_async();
                #pragma unroll 1
                for (int i = 0; i < 2; i++, n++) { STG_WAIT(n); bulk_ld(STG_ADDR(n), op + i * 8192, 8192, STG_FULL(n)); }
                mbar_sleep(bar_kfull + 40, 0);
                fence_async();
                uint32_t k0 = 28 * ct;
                #pragma unroll 1
                for (int i = 0; i < 14; i++, n++) {
                    if (i == 3) { flag_wait(F_H + rb, 4); fence_async(); }
                    STG_WAIT(n);
                    const uint32_t nb = (i == 13 || k0 == 104) ? 4096 : 8192;
                    bulk_ld(STG_ADDR(n), hp + k0 * 1024, nb, STG_FULL(n));
                    if (k0 == 104 && i != 13) bulk_ld(STG_ADDR(n) + 4096, hp, 4096, STG_FULL(n));
                    k0 += 8; if (k0 >= 108) k0 -= 108;
                }
                #pragma unroll 1
                for (int i = 2; i < 10; i++, n++) {
                    if (i == 2 || i == 6) { flag_wait(F_O + rb * 3 + (i == 2 ? 1 : 2), i == 2 ? 4 : 12); fence_async(); }
                    STG_WAIT(n);
                    bulk_ld(STG_ADDR(n), op + i * 8192, 8192, STG_FULL(n));
                }
            }
        } else if (wu == 1) {
            if (elect_one()) {
                flag_wait(F_KV, 32);
                asm volatile("fence.proxy.async.global;" ::: "memory");
                TRW(19);
                mbar_expect(bar_kfull + 32, 3072 + 512);
                bulk_ld(sb + SM_KV + 3 * KST_BYTES + 6144, g_kv + 31 * 6144, 3072, bar_kfull + 32);
                bulk_ld(sb + SM_MISC + 512, g_kvmax, 256, bar_kfull + 32);
                bulk_ld(sb + SM_MISC + 256, g_gate + rb * 64, 256, bar_kfull + 32);
                #pragma unroll 1
                for (int i = 0; i < 48; i++) {
                    const uint32_t st = i & 3;
                    if (i >= 3) mbar_sleep(bar_kempty + 8 * st, (((i + 1) >> 2) & 1) ^ 1);
                    mbar_expect(bar_kfull + 8 * st, KST_BYTES);
                    bulk_ld_mc(sb + SM_KV + st * KST_BYTES + rank * 6144, g_kv + (i & 15) * KST_BYTES + rank * 6144, 6144, bar_kfull + 8 * st);
                    if (i == 19 || i == 35) flag_add(F_O + rb * 3 + (i == 35));
                }
            }
        } else {
            if (ct == 3) {
                bar_sync(10, 160);
                if (lane < 2) {
                    const float* r = s_red + 8 + 4 * lane;
                    g_kvmax[lane * 32 + rb] = __uint_as_float(max(max(__float_as_uint(r[0]), __float_as_uint(r[1])), max(__float_as_uint(r[2]), __float_as_uint(r[3]))));
                }
                __syncwarp();
                if (elect_one()) flag_add(F_KV);
                __syncwarp();
            }
            bar_sync(10, 160);
            if (elect_one()) { flag_add(F_H + rb); mbar_arrive(bar_kfull + 40); }
        }
    } else if (wg == 3) {
        asm volatile("setmaxnreg.inc.sync.aligned.u32 144;");
        TRACE(0);
        GemmCtx c{{0, 0}, ((sb + SM_G) & 0x3FFFFu) >> 4, bar_gfull, bar_gempty, peer_off, lane == 0};
        const OpDesc a_sw{0u, 64u | (1u << 30), 2u, 0u, 0u};
        const OpDesc a_t{64u << 16, 8u, 128u, 0u, 0u};
        const OpDesc b_q{512u | (128u << 16), 32u | (2u << 30), 64u, 640u, 384u};
        const OpDesc b_w{512u | (128u << 16), 32u | (2u << 30), 64u, 896u, 512u};
        const OpDesc b_z{512u | (224u << 16), 8u, 448u, 896u, 128u};
        const OpDesc b_o{512u | (160u << 16), 8u, 320u, 640u, 96u};
        const int r0 = 16 * w + g;
        if (ct == 3) {
            float ex[24];
            const uint32_t exlo = (((sb + SM_KV) & 0x3FFFFu) >> 4) | (48u << 16);
            bar_sync(1, 512);
            #pragma unroll 1
            for (int kb = 0; kb < 10; kb++) {
                if ((kb & 3) == 0) mbar_wait(bar_gfull + 8 * (kb >> 2), 0);
                const uint32_t base = c.sb16 + (kb >> 2) * (GST_BYTES / 16) + (kb & 3) * 512;
                wg_fence();
                #pragma unroll
                for (int k = 0; k < 4; k++) wgmma_ss_n48<0, 1>(ex, mkdesc(base + 2 * k, a_sw.hi), mkdesc(exlo + (kb * 4 + k) * 96, 8), (k > 0) | (kb > 0));
                wg_commit();
            }
            wg_wait<0>();
            FENCE_F(ex, 24);
            if (lane < 4) release2(bar_gempty + 8 * lane, peer_off);
            c.r.ph = 1;
            uint8_t* dk = g_kv + ((rb + 31) & 31) * 6144 + 2 * w * 384 + g * 16 + t * 4;
            uint8_t* dv = g_kv + rb * 6144 + 3072 + 2 * w * 384 + g * 16 + t * 4;
            uint32_t mk = 0, mv = 0;
            #pragma unroll
            for (int hi = 0; hi < 2; hi++) {
                const bool alu = (PAT >> (2 * w + hi)) & 1;
                float n2 = 0.f;
                #pragma unroll
                for (int j = 0; j < 3; j++) {
                    uint32_t v = pack_bf16(ex[4 * j + 2 * hi], ex[4 * j + 2 * hi + 1]);
                    const float a = bf_lo(v), b = bf_hi(v);
                    n2 = fmaf(a, a, fmaf(b, b, n2));
                    if (alu) v = pack_bf16(2.f * a, 2.f * b);
                    if (j == 2 && t == 2) v = alu ? 0x3C004440u : 0x39A93FCBu;
                    *(uint32_t*)(dk + hi * 384 + j * 128) = v;
                    v = pack_bf16(ex[12 + 4 * j + 2 * hi], ex[12 + 4 * j + 2 * hi + 1]);
                    if (j < 2 || t < 2) mv = max(mv, max((v << 16) & 0x7FFF0000u, v & 0x7FFF0000u));
                    if (j == 2 && t == 3) {
                        g_gate[rb * 64 + r0 + 8 * hi] = 1.f / (1.f + __expf(-ex[20 + 2 * hi]));
                        v = 0u;
                    }
                    if (j == 2 && t == 2) v = 0x00003F80u;
                    *(uint32_t*)(dv + hi * 384 + j * 128) = v;
                }
                n2 += __shfl_xor_sync(0xffffffffu, n2, 1); n2 += __shfl_xor_sync(0xffffffffu, n2, 2);
                mk = max(mk, __float_as_uint(n2) & 0x7FFFFFFFu);
            }
            mk = __reduce_max_sync(0xffffffffu, mk); mv = __reduce_max_sync(0xffffffffu, mv);
            if (lane == 0) { s_red[8 + w] = __uint_as_float(mk); s_red[12 + w] = __uint_as_float(mv); }
            bar_arrive(10, 160);
            TRACE(15);
        }
        {
            float acc[80];
            gemm_loop<160, 4, 0>(acc, 10, 1, a_sw, b_q, c);
            TRACE(1);
            uint8_t* qs = sm + SM_Q + 2 * w * 128 + g * 16;
            #pragma unroll
            for (int j = 0; j < 20; j++) {
                constexpr int dummy = 0; (void)dummy;
                const int h0 = (8 * j) / 20, d0 = (8 * j) % 20, d = d0 + 2 * t;
                const int off = d < 20 ? h0 * 3072 + (d >> 3) * 1024 + (d & 7) * 2 : (h0 + 1) * 3072 + (d - 20) * 2;
                *(uint32_t*)(qs + off) = pack_bf16(acc[4 * j] * 0.3225964182229561f, acc[4 * j + 1] * 0.3225964182229561f);
                *(uint32_t*)(qs + off + 128) = pack_bf16(acc[4 * j + 2] * 0.3225964182229561f, acc[4 * j + 3] * 0.3225964182229561f);
            }
            bar_arrive(2, 384);
            bar_arrive(13, 256);
        }
        {
            float acc[112];
            #pragma unroll
            for (int i = 96; i < 112; i++) acc[i] = 0.f;
            #define GEMM_Z(GBX, nkb, first, bd) { if (ct == 3) gemm_loop<192, 4, GBX>(*(float(*)[96])&acc[0], nkb, first, a_sw, bd, c); \
                                                  else gemm_loop<224, 4, GBX>(acc, nkb, first, a_sw, bd, c); }
            GEMM_Z(GB2, 10, 1, b_w)
            TRACE(2);
            uint4* z1p = g_z1 + (size_t)blockIdx.x * 14 * 128 + tid;
            {
                float s0 = 0.f, q0 = 0.f, s1 = 0.f, q1 = 0.f;
                #pragma unroll
                for (int j = 0; j < 14; j++) {
                    float y[8];
                    #pragma unroll
                    for (int i = 0; i < 8; i++) y[i] = gelu2_tanh(acc[8 * j + i]);
                    s0 += (y[0] + y[1]) + (y[4] + y[5]); q0 = fmaf(y[0], y[0], fmaf(y[1], y[1], fmaf(y[4], y[4], fmaf(y[5], y[5], q0))));
                    s1 += (y[2] + y[3]) + (y[6] + y[7]); q1 = fmaf(y[2], y[2], fmaf(y[3], y[3], fmaf(y[6], y[6], fmaf(y[7], y[7], q1))));
                    z1p[(NCTA * 14 + j) * 128] = make_uint4(pack_bf16(y[0], y[1]), pack_bf16(y[2], y[3]), pack_bf16(y[4], y[5]), pack_bf16(y[6], y[7]));
                }
                #pragma unroll
                for (int o = 1; o <= 2; o <<= 1) {
                    s0 += __shfl_xor_sync(0xffffffffu, s0, o); q0 += __shfl_xor_sync(0xffffffffu, q0, o);
                    s1 += __shfl_xor_sync(0xffffffffu, s1, o); q1 += __shfl_xor_sync(0xffffffffu, q1, o);
                }
                if (t < 2) asm volatile("st.relaxed.gpu.global.v4.u32 [%0], {%1, %2, %3, %3};" :: "l"(&g_part[(rb * 4 + ct) * 64 + r0 + 8 * t]),
                                        "r"(__float_as_uint(t ? s1 : s0)), "r"(__float_as_uint(t ? q1 : q0)), "r"(1u) : "memory");
            }
            bar_arrive(11, 256);
            TRACE(3);
            GEMM_Z(GB3, 10, 1, b_w)
            TRACE(4);
            #pragma unroll
            for (int j = 0; j < 14; j++)
                z1p[j * 128] = make_uint4(pack_bf16(gelu2_tanh(acc[8 * j]), gelu2_tanh(acc[8 * j + 1])), pack_bf16(gelu2_tanh(acc[8 * j + 2]), gelu2_tanh(acc[8 * j + 3])),
                                          pack_bf16(gelu2_tanh(acc[8 * j + 4]), gelu2_tanh(acc[8 * j + 5])), pack_bf16(gelu2_tanh(acc[8 * j + 6]), gelu2_tanh(acc[8 * j + 7])));
            TRACE(7);
            const float b0 = __bfloat162float(p.bsp[rb * 64 + r0]), b1 = __bfloat162float(p.bsp[rb * 64 + r0 + 8]);
            GEMM_Z(GB4, 32, 1, b_z)
            TRACE(8);
            bar_sync(8, 512);
            const float g0 = 0.5f - 0.5f * s_gate[r0], g1 = 0.5f - 0.5f * s_gate[r0 + 8];
            {
                mbar_wait(c.bar_full + 8 * c.r.st, c.r.ph);
                const uint4* zs = (const uint4*)(sm + SM_G + c.r.st * GST_BYTES) + tid;
                uint8_t* dst = g_hp + (size_t)((rb * 108 + 28 * ct) * 8 + 2 * w) * 128 + g * 16 + t * 4;
                const float e0 = b0 * g0, e1 = b1 * g1;
                #pragma unroll
                for (int j = 0; j < 14; j++) {
                    if (j < 12 || ct < 3) {
                        const uint4 v = zs[j * 128];
                        *(uint32_t*)(dst + (2 * j) * 1024) = pack_bf16(fmaf(acc[8 * j], g0, e0) * bf_lo(v.x), fmaf(acc[8 * j + 1], g0, e0) * bf_hi(v.x));
                        *(uint32_t*)(dst + (2 * j) * 1024 + 128) = pack_bf16(fmaf(acc[8 * j + 2], g1, e1) * bf_lo(v.y), fmaf(acc[8 * j + 3], g1, e1) * bf_hi(v.y));
                        *(uint32_t*)(dst + (2 * j + 1) * 1024) = pack_bf16(fmaf(acc[8 * j + 4], g0, e0) * bf_lo(v.z), fmaf(acc[8 * j + 5], g0, e0) * bf_hi(v.z));
                        *(uint32_t*)(dst + (2 * j + 1) * 1024 + 128) = pack_bf16(fmaf(acc[8 * j + 6], g1, e1) * bf_lo(v.w), fmaf(acc[8 * j + 7], g1, e1) * bf_hi(v.w));
                    }
                }
                __syncwarp();
                if (c.lead) release2(c.bar_empty + 8 * c.r.st, c.peer_off);
                ring_next<GST>(c.r);
            }
            bar_arrive(10, 160);
            TRACE(9);
        }
        {
            float acc[80];
            gemm_loop<160, 4, GB5>(acc, 15, 1, a_t, b_o, c);
            gemm_loop<160, 2, GB5>(acc, 1, 0, a_t, b_o, c);
            gemm_loop<160, 4, GB5>(acc, 4, 0, a_t, b_o, c);
            TRACE(10);
            gemm_loop<160, 4, 0>(acc, 4, 0, a_t, b_o, c);
            TRACE(11);
            uint32_t* os = (uint32_t*)(sm + SM_Q) + r0 * (QS_PITCH / 2) + t;
            #pragma unroll
            for (int j = 0; j < 20; j++) {
                os[4 * j] = pack_bf16(acc[4 * j], acc[4 * j + 1]);
                os[8 * (QS_PITCH / 2) + 4 * j] = pack_bf16(acc[4 * j + 2], acc[4 * j + 3]);
            }
            asm volatile("fence.proxy.async.shared::cta;" ::: "memory");
            __syncwarp();
            if (lane < 16) {
                const int row = 16 * w + lane;
                asm volatile("cp.async.bulk.global.shared::cta.bulk_group [%0], [%1], 320;"
                             :: "l"(p.out + (size_t)(rb * 64 + row) * DM + 160 * ct), "r"(sb + SM_Q + row * (QS_PITCH * 2)) : "memory");
                asm volatile("cp.async.bulk.commit_group;\ncp.async.bulk.wait_group 0;" ::: "memory");
            }
            TRACE(12);
            if (tid < 64) g_part[(rb * 4 + ct) * 64 + tid] = make_uint4(0u, 0u, 0u, 0u);
            if (tid == 0) {
                unsigned d = atomicAdd(&g_flags[F_DONE * 8], 1u);
                if (d == NCTA - 1) { for (int i = 0; i < F_NUM; i++) g_flags[i * 8] = 0; }
            }
            __syncwarp();
            asm volatile("barrier.cluster.arrive.relaxed;\nbarrier.cluster.wait;" ::: "memory");
            TRACE(20);
        }
    } else {
        asm volatile("setmaxnreg.inc.sync.aligned.u32 104;");
        const int atid = threadIdx.x;
        {
            *(uint2*)(sm + SM_Q + 8 * 3072 + (atid & 127) * 8) = make_uint2(0u, 0u);
            if (ct < 3) {
                uint4 w1[2], w2[2];
                const int c1 = blockIdx.x * 67, c2 = blockIdx.x * 90;
                retile_ld<2, 48>(w1, p.wo, DM, 80, 80, c1, 67, atid);
                retile_ld<2, 48>(w2, p.wout, DM, 80, 108, c2, 90, atid);
                retile_st<20, 2, 48, true>(w1, 80, 80, g_wot, c1, 67, atid);
                retile_st<20, 2, 48, false>(w2, 80, 108, g_woutt, c2, 90, atid);
                bar_sync(9, 384);
                if (atid == 256) flag_add(F_WR);
            } else {
                mbar_wait(bar_kfull + 48, 0);
                #pragma unroll 2
                for (int e = atid; e < 1280; e += 384) {
                    const int m = e >= 640, k = e - m * 640;
                    const uint2* src = (const uint2*)(sm + SM_W + e * 40);
                    const uint2 a = src[0], b = src[1], c = src[2], d = src[3], f = src[4];
                    const uint32_t gt = m ? *(const unsigned short*)(sm + SM_W + 51200 + k * 2) : 0u;
                    uint4* dst = (uint4*)(sm + SM_KV + (k >> 3) * 768 + (k & 7) * 16 + m * 384);
                    dst[0] = make_uint4(a.x, a.y, b.x, b.y); dst[8] = make_uint4(c.x, c.y, d.x, d.y); dst[16] = make_uint4(f.x, f.y, 0u, gt);
                }
                asm volatile("fence.proxy.async.shared::cta;" ::: "memory");
                bar_arrive(1, 512);
                if (wg == 0) TRACE(13);
            }
        }
        const uint32_t half2c = *(const volatile uint32_t*)&g_const[2];
        if (wg == 2) {
            const int r0 = 16 * w + g;
            uint4* z1p = g_z1 + (size_t)blockIdx.x * 14 * 128 + tid;
            uint4 v[14];
            bar_sync(11, 256);
            #pragma unroll
            for (int j = 0; j < 14; j++) v[j] = __ldcg(z1p + (NCTA * 14 + j) * 128);
            float s0, q0, s1, q1;
            {
                uint4 a, b;
                const uint4* pa_ = &g_part[(rb * 4 + t) * 64 + r0];
                #pragma unroll 1
                for (int it = 0; ; it++) {
                    asm volatile("ld.relaxed.gpu.global.v4.u32 {%0, %1, %2, %3}, [%4];" : "=r"(a.x), "=r"(a.y), "=r"(a.z), "=r"(a.w) : "l"(pa_) : "memory");
                    asm volatile("ld.relaxed.gpu.global.v4.u32 {%0, %1, %2, %3}, [%4];" : "=r"(b.x), "=r"(b.y), "=r"(b.z), "=r"(b.w) : "l"(pa_ + 8) : "memory");
                    if (__all_sync(0xffffffffu, (a.z & b.z) != 0)) break;
                    if (it > SPIN_LIMIT) SPIN_FAIL(F_STAT);
                    __nanosleep(100);
                }
                s0 = __uint_as_float(a.x); q0 = __uint_as_float(a.y); s1 = __uint_as_float(b.x); q1 = __uint_as_float(b.y);
                #pragma unroll
                for (int o = 1; o <= 2; o <<= 1) {
                    s0 += __shfl_xor_sync(0xffffffffu, s0, o); q0 += __shfl_xor_sync(0xffffffffu, q0, o);
                    s1 += __shfl_xor_sync(0xffffffffu, s1, o); q1 += __shfl_xor_sync(0xffffffffu, q1, o);
                }
            }
            TRACE(5);
            const float m0 = s0 * (1.f / FH), m1 = s1 * (1.f / FH);
            const float rs0 = rsqrtf(fmaxf(q0 * (1.f / FH) - m0 * m0, 0.f) + 4e-5f), rs1 = rsqrtf(fmaxf(q1 * (1.f / FH) - m1 * m1, 0.f) + 4e-5f);
            const float c0 = -m0 * rs0, c1 = -m1 * rs1;
            uint8_t* dst = g_z2n + (size_t)(ct * 32 + rb) * 28672 + (2 * w) * 3584 + g * 16 + t * 4;
            #pragma unroll
            for (int j = 0; j < 14; j++) {
                *(uint32_t*)(dst + 2 * j * 128) = pack_bf16(fmaf(bf_lo(v[j].x), rs0, c0), fmaf(bf_hi(v[j].x), rs0, c0));
                *(uint32_t*)(dst + 3584 + 2 * j * 128) = pack_bf16(fmaf(bf_lo(v[j].y), rs1, c1), fmaf(bf_hi(v[j].y), rs1, c1));
                *(uint32_t*)(dst + (2 * j + 1) * 128) = pack_bf16(fmaf(bf_lo(v[j].z), rs0, c0), fmaf(bf_hi(v[j].z), rs0, c0));
                *(uint32_t*)(dst + 3584 + (2 * j + 1) * 128) = pack_bf16(fmaf(bf_lo(v[j].w), rs1, c1), fmaf(bf_hi(v[j].w), rs1, c1));
            }
            bar_sync(6, 128);
            if (tid == 0) flag_add(F_Z2 + rb * 4 + ct);
            TRACE(6);
            TRACE(14);
        }
        if (wg == 2) bar_sync(13, 256); else bar_sync(2, 384);
        const int p0 = wg == 2 ? 1 : 0;
        #define HEAD(ps) ((ps) == 0 ? wg : 3 * (ps) - 1 + wg)
        uint32_t qmax2 = 0;
        #pragma unroll 1
        for (int i = p0 + (tid >> 6); i < 3; i += 2) {
            uint8_t* qrow = sm + SM_Q + HEAD(i) * 3072 + (tid & 63) * 16;
            const uint4 a = *(const uint4*)qrow, b = *(const uint4*)(qrow + 1024);
            const uint2 c = *(const uint2*)(qrow + 2048);
            #define SQ(v) (bf_lo(v) * bf_lo(v) + bf_hi(v) * bf_hi(v))
            const float n = SQ(a.x) + SQ(a.y) + SQ(a.z) + SQ(a.w) + SQ(b.x) + SQ(b.y) + SQ(b.z) + SQ(b.w) + SQ(c.x) + SQ(c.y);
            qmax2 = max(qmax2, __float_as_uint(n) & 0x7FFFFFFFu);
            *(uint2*)(qrow + 2048 + 8) = make_uint2(0x3F803F80u, 0u);
        }
        asm volatile("fence.proxy.async.shared::cta;" ::: "memory");
        mbar_sleep(bar_kfull + 32, 0);
        bar_arrive(8, 512);
        uint32_t safe;
        {
            const float kmax2 = __uint_as_float(__reduce_max_sync(0xffffffffu, __float_as_uint(s_stat[lane])));
            const int ev = (int)(__reduce_max_sync(0xffffffffu, __float_as_uint(s_stat[32 + lane])) >> 23) - 126;
            const float bmax = fminf(100.f, fminf((float)(110 - max(ev, 1)), (float)(88 + ev)));
            const bool ok = bmax > 0.f && __uint_as_float(qmax2) * kmax2 <= bmax * bmax;
            asm volatile("{\n.reg .pred p, q;\nsetp.ne.u32 p, %1, 0;\nbarrier.red.and.pred.aligned q, %2, 128, p;\nselp.u32 %0, 1, 0, q;\n}"
                         : "=r"(safe) : "r"((uint32_t)ok), "r"(4 + wg) : "memory");
            safe = __shfl_sync(0xffffffffu, safe, 0);
            if (!safe) {
                #pragma unroll 1
                for (int i = p0 + (tid >> 6); i < 3; i += 2) *(uint2*)(sm + SM_Q + HEAD(i) * 3072 + (tid & 63) * 16 + 2048 + 8) = make_uint2(0u, 0u);
                asm volatile("fence.proxy.async.shared::cta;" ::: "memory");
                bar_sync(4 + wg, 128);
            }
        }
        const uint32_t kv16 = ((sb + SM_KV) & 0x3FFFFu) >> 4;
        constexpr uint32_t KLBO = 8u << 16, KHI = 24u, VLBO = (24u << 16) + 192u, VHI = 8u;
        const bool lead = lane == 0;
        const int r0 = 16 * w + g;
        static_assert(KST == 4, "ring phases below assume 4 stages");
        if (wg == 2) {
            bar_sync(14, 256);
            mbar_wait(bar_kfull + 24, 1);
        }
        const uint32_t q16 = ((sb + SM_Q) & 0x3FFFFu) >> 4;
        uint64_t qa = mkdesc(q16 + HEAD(p0) * 192 + (64u << 16), 8), qb = mkdesc(q16 + HEAD(p0) * 192 + 128 + ((uint32_t)(1536 - 128 - HEAD(p0) * 192) << 16), 8);
        #define NEXT_HEAD(ps) { const uint32_t d_ = (ps) == 0 ? 384 : 576; qa += d_; qb += (uint64_t)d_ - ((uint64_t)d_ << 16); }
        const uint64_t dk = mkdesc(kv16 + KLBO, KHI), dv = mkdesc(kv16 + VLBO, VHI);
        const uint32_t kep = bar_kempty + peer_off;
        uint32_t rc = lead ? (wg == 0 ? 2 : 1) : 0;
        float o[12];
        #pragma unroll
        for (int i = 0; i < 12; i++) o[i] = 0.f;
        float s[32]; uint32_t pa[16], pb[16];
        FENCE_F(o, 12);
        #define QK(off) wgmma_ss_n64<0, 0>(s, qa, dk + (off), 0); wgmma_ss_n64<0, 0>(s, qb, dk + (off) + 16, 1);
        #define PV(pp, off) wgmma_rs_n24<1>(o, pp[0], pp[1], pp[2], pp[3], dv + (off), 1); wgmma_rs_n24<1>(o, pp[4], pp[5], pp[6], pp[7], dv + (off) + 48, 1); \
                            wgmma_rs_n24<1>(o, pp[8], pp[9], pp[10], pp[11], dv + (off) + 96, 1); wgmma_rs_n24<1>(o, pp[12], pp[13], pp[14], pp[15], dv + (off) + 144, 1);
        #define STORE_O(h) { \
            const float l0 = __shfl_sync(0xffffffffu, o[8], (lane & ~3) | 2), l1 = __shfl_sync(0xffffffffu, o[10], (lane & ~3) | 2); \
            const float i0 = __fdividef(s_gate[r0], l0), i1 = __fdividef(s_gate[r0 + 8], l1);        \
            _Pragma("unroll") for (int b = 0; b < 3; b++) { \
                if (b < 2 || t < 2) { \
                    const int cq = 20 * (h) + 8 * b + 2 * t, col = cq < 32 ? ct * 32 + cq : (cq < 96 ? 96 + ct * 64 + cq : 288 + ct * 64 + cq); \
                    uint8_t* dst = g_op + (size_t)((rb * 80 + (col >> 3)) * 8 + 2 * w) * 128 + g * 16 + (col & 7) * 2; \
                    *(uint32_t*)dst = pack_bf16(o[4 * b] * i0, o[4 * b + 1] * i0); \
                    *(uint32_t*)(dst + 128) = pack_bf16(o[4 * b + 2] * i1, o[4 * b + 3] * i1); \
                } \
            } \
            _Pragma("unroll") for (int i = 0; i < 12; i++) o[i] = 0.f; \
            FENCE_F(o, 12); \
            __syncwarp(); \
            TRACE(22 + (h)); }
        if (safe) {
            wg_fence();
            QK(3 * 768 + 384)
            wg_commit();
            TRACE(16 + wg);
            wg_wait<0>();
            FENCE_F(s, 32);
            release2n(bar_kempty + 24, kep + 24, rc);
            EXPBLK(pa, s);
            FENCE_R(pa, 16);
            #define HALF(off, pin, pout) \
                wg_fence(); \
                QK(off) \
                wg_commit(); \
                PV(pin, off) \
                wg_commit(); \
                wg_wait<1>(); \
                FENCE_F(s, 32); \
                EXPBLK(pout, s); \
                FENCE_R(pout, 16); \
                wg_wait<0>();
            #pragma unroll 1
            for (int J4 = 4 * p0; J4 < 12; J4++) {
                const uint32_t ph = J4 & 1;
                #pragma unroll
                for (int st = 0; st < 4; st++) {
                    mbar_wait(bar_kfull + 8 * st, ph);
                    if (st == 3 && J4 == 3 && wg == 0) bar_arrive(14, 256);
                    HALF(st * 768, pa, pb)
                    if (st == 3 && (J4 & 3) == 3 && J4 < 11) NEXT_HEAD(J4 >> 2)
                    HALF(st * 768 + 384, pb, pa)
                    if (st < 3) release2n(bar_kempty + 8 * st, kep + 8 * st, rc);
                }
                if ((J4 & 3) == 3) {
                    FENCE_F(o, 12);
                    STORE_O(HEAD(J4 >> 2))
                    rc = lead ? 1 : 0;
                }
                release2n(bar_kempty + 24, kep + 24, rc);
            }
        } else {
            float m0 = -INFINITY, m1 = -INFINITY;
            #pragma unroll 1
            for (int u = 32 * p0; u < 96; u++) {
                const int J = u >> 1;
                if ((u & 1) == 0) mbar_wait(bar_kfull + 8 * (J & 3), (J >> 2) & 1);
                if (u == 30 && wg == 0) bar_arrive(14, 256);
                wg_fence();
                QK(((u + 7) & 7) * 384)
                wg_commit();
                wg_wait<0>();
                FENCE_F(s, 32);
                float x0 = m0, x1 = m1;
                #pragma unroll
                for (int b = 0; b < 8; b++) {
                    const float f = ((PAT >> b) & 1) ? 0.5f : 1.f;
                    s[4 * b] *= f; s[4 * b + 1] *= f; s[4 * b + 2] *= f; s[4 * b + 3] *= f;
                    x0 = fmaxf(x0, fmaxf(s[4 * b], s[4 * b + 1])); x1 = fmaxf(x1, fmaxf(s[4 * b + 2], s[4 * b + 3]));
                }
                x0 = fmaxf(x0, __shfl_xor_sync(0xffffffffu, x0, 1)); x0 = fmaxf(x0, __shfl_xor_sync(0xffffffffu, x0, 2));
                x1 = fmaxf(x1, __shfl_xor_sync(0xffffffffu, x1, 1)); x1 = fmaxf(x1, __shfl_xor_sync(0xffffffffu, x1, 2));
                const float f0 = exp2f(m0 - x0), f1 = exp2f(m1 - x1);
                m0 = x0; m1 = x1;
                #pragma unroll
                for (int b = 0; b < 3; b++) { o[4 * b] *= f0; o[4 * b + 1] *= f0; o[4 * b + 2] *= f1; o[4 * b + 3] *= f1; }
                #pragma unroll
                for (int b = 0; b < 8; b++) {
                    pa[2 * b] = exp2_mufu(s[4 * b] - m0, s[4 * b + 1] - m0);
                    pa[2 * b + 1] = exp2_mufu(s[4 * b + 2] - m1, s[4 * b + 3] - m1);
                }
                FENCE_R(pa, 16); FENCE_F(o, 12);
                wg_fence();
                PV(pa, (u & 7) * 384)
                wg_commit();
                wg_wait<0>();
                FENCE_F(o, 12);
                if ((u & 1) == 0) release2n(bar_kempty + 8 * ((J + 3) & 3), kep + 8 * ((J + 3) & 3), rc);
                if ((u & 31) == 31) {
                    STORE_O(HEAD(u >> 5))
                    m0 = -INFINITY; m1 = -INFINITY;
                    NEXT_HEAD(u >> 5)
                    rc = lead ? 1 : 0;
                }
            }
        }
        bar_sync(4 + wg, 128);
        if (tid == 0) flag_add(F_O + rb * 3 + 2);
    }
}

typedef CUresult (*EncodeFn)(CUtensorMap*, CUtensorMapDataType, cuuint32_t, void*, const cuuint64_t*, const cuuint64_t*, const cuuint32_t*,
                             const cuuint32_t*, CUtensorMapInterleave, CUtensorMapSwizzle, CUtensorMapL2promotion, CUtensorMapFloatOOBfill);

void make_map(EncodeFn fn, CUtensorMap* m, const void* ptr, uint64_t cols, uint64_t rows, uint32_t bc, uint32_t br, CUtensorMapSwizzle sw) {
    cuuint64_t dims[2] = {cols, rows}, strides[1] = {cols * 2};
    cuuint32_t box[2] = {bc, br}, es[2] = {1, 1};
    fn(m, CU_TENSOR_MAP_DATA_TYPE_BFLOAT16, 2, const_cast<void*>(ptr), dims, strides, box, es, CU_TENSOR_MAP_INTERLEAVE_NONE, sw,
       CU_TENSOR_MAP_L2_PROMOTION_L2_128B, CU_TENSOR_MAP_FLOAT_OOB_FILL_NONE);
}

void make_map3(EncodeFn fn, CUtensorMap* m, const void* ptr, uint64_t cols, uint64_t rows, uint32_t natoms) {
    cuuint64_t dims[3] = {32, rows, cols / 32}, strides[2] = {cols * 2, 64};
    cuuint32_t box[3] = {32, 32, natoms}, es[3] = {1, 1, 1};
    fn(m, CU_TENSOR_MAP_DATA_TYPE_BFLOAT16, 3, const_cast<void*>(ptr), dims, strides, box, es, CU_TENSOR_MAP_INTERLEAVE_NONE, CU_TENSOR_MAP_SWIZZLE_64B,
       CU_TENSOR_MAP_L2_PROMOTION_L2_128B, CU_TENSOR_MAP_FLOAT_OOB_FILL_NONE);
}

}

extern "C" void kernel_launch(void* const* d_in, const int* in_sizes, int n_in, void* d_out, int out_size) {
    static EncodeFn fn = nullptr;
    if (!fn) {
        cudaDriverEntryPointQueryResult qr;
        void* f = nullptr;
        cudaGetDriverEntryPoint("cuTensorMapEncodeTiled", &f, cudaEnableDefault, &qr);
        fn = (EncodeFn)f;
        cudaFuncSetAttribute(mega_kernel, cudaFuncAttributeMaxDynamicSharedMemorySize, SM_TOTAL);
    }
    Params p;
    const __nv_bfloat16* x = (const __nv_bfloat16*)d_in[0];
    make_map(fn, &p.mx, x, DM, S_LEN, 64, 64, CU_TENSOR_MAP_SWIZZLE_128B);
    make_map(fn, &p.mwsp, d_in[7], S_LEN, S_LEN, 64, 64, CU_TENSOR_MAP_SWIZZLE_128B);
    make_map3(fn, &p.mwq, d_in[1], DM, DM, 5);
    make_map3(fn, &p.mwin, d_in[6], 2 * FH, DM, 7);
    p.x = x;
    p.wq = (const __nv_bfloat16*)d_in[1];
    p.win = (const __nv_bfloat16*)d_in[6];
    p.wk = (const __nv_bfloat16*)d_in[2];
    p.wv = (const __nv_bfloat16*)d_in[3];
    p.bsp = (const __nv_bfloat16*)d_in[8];
    p.gw = (const __nv_bfloat16*)d_in[10];
    p.wsp = (const __nv_bfloat16*)d_in[7];
    p.wo = (const __nv_bfloat16*)d_in[4];
    p.wout = (const __nv_bfloat16*)d_in[9];
    p.out = (__nv_bfloat16*)d_out;
    mega_kernel<<<NCTA, 640, SM_TOTAL>>>(p);
}
```

```cpp
#include <cuda_runtime.h>
#include <cuda_bf16.h>
#include <cuda.h>
#include <stdint.h>

namespace {

constexpr int S_LEN = 2048, DM = 640, FH = 864;
constexpr int NCTA = 128;
#define PAT8 0xB5u
constexpr uint32_t PAT = PAT8 * 0x101u;
#define GB2 -1
#define GB3 -1
#define GB4 2
#define GB5 -1
constexpr int GST = 4;
constexpr int GST_BYTES = 36864;
constexpr int KST = 4;
constexpr int KST_BYTES = 12288;
constexpr int QS_PITCH = 168;
constexpr int SM_G = 0;
constexpr int SM_KV = SM_G + GST * GST_BYTES;
constexpr int SM_Q = SM_KV + KST * KST_BYTES;
constexpr int SM_MISC = SM_Q + 8 * 3072 + 1024;
constexpr int SM_W = SM_G + 2 * GST_BYTES + 16384;
constexpr int SM_TOTAL = SM_MISC + 2048 + 1024;

constexpr int F_KV = 0, F_DONE = 1, F_WR = 2, F_Z2 = 3, F_H = F_Z2 + 128, F_O = F_H + 32, F_NUM = F_O + 96;

__device__ __align__(1024) uint8_t g_kv[16 * KST_BYTES];
__device__ __align__(1024) uint8_t g_z2n[4 * 32 * 28672];
__device__ __align__(1024) uint8_t g_hp[32 * 108 * 1024];
__device__ __align__(1024) uint8_t g_op[32 * 80 * 1024];
__device__ __align__(1024) uint8_t g_wot[4 * 80 * 2560];
__device__ __align__(1024) uint8_t g_woutt[4 * 108 * 2560];
__device__ __align__(1024) uint4 g_z1[2 * NCTA * 14 * 128];
__device__ unsigned long long g_part[32 * 4 * 64];
__device__ __align__(128) float g_kvmax[64];
__device__ __align__(128) float g_gate[S_LEN];
__device__ unsigned g_flags[F_NUM * 8];
__device__ uint32_t g_const[1] = {0x3F013F01u};

struct Params {
    CUtensorMap mx, mwsp, mwq, mwin;
    const __nv_bfloat16 *x, *wk, *wv, *bsp, *gw, *wsp, *wo, *wout, *wq, *win;
    __nv_bfloat16* out;
};

template<int TB> __device__ __forceinline__ void wgmma_rs_n24(float (&d)[12], uint32_t a0, uint32_t a1, uint32_t a2, uint32_t a3, uint64_t db, int scale_d) {
  asm volatile("{\n.reg .pred p;\nsetp.ne.b32 p, %17, 0;\nwgmma.mma_async.sync.aligned.m64n24k16.f32.bf16.bf16 {%0,%1,%2,%3,%4,%5,%6,%7,%8,%9,%10,%11}, {%12,%13,%14,%15}, %16, p, 1, 1, %18;\n}"
    : "+f"(d[0]), "+f"(d[1]), "+f"(d[2]), "+f"(d[3]), "+f"(d[4]), "+f"(d[5]), "+f"(d[6]), "+f"(d[7]), "+f"(d[8]), "+f"(d[9]), "+f"(d[10]), "+f"(d[11])
    : "r"(a0), "r"(a1), "r"(a2), "r"(a3), "l"(db), "r"(scale_d), "n"(TB));
}
template<int TA, int TB> __device__ __forceinline__ void wgmma_ss_n48(float (&d)[24], uint64_t da, uint64_t db, int scale_d) {
  asm volatile("{\n.reg .pred p;\nsetp.ne.b32 p, %26, 0;\nwgmma.mma_async.sync.aligned.m64n48k16.f32.bf16.bf16 {%0,%1,%2,%3,%4,%5,%6,%7,%8,%9,%10,%11,%12,%13,%14,%15,%16,%17,%18,%19,%20,%21,%22,%23}, %24, %25, p, 1, 1, %27, %28;\n}"
    : "+f"(d[0]), "+f"(d[1]), "+f"(d[2]), "+f"(d[3]), "+f"(d[4]), "+f"(d[5]), "+f"(d[6]), "+f"(d[7]), "+f"(d[8]), "+f"(d[9]), "+f"(d[10]), "+f"(d[11]), "+f"(d[12]), "+f"(d[13]), "+f"(d[14]), "+f"(d[15]), "+f"(d[16]), "+f"(d[17]), "+f"(d[18]), "+f"(d[19]), "+f"(d[20]), "+f"(d[21]), "+f"(d[22]), "+f"(d[23])
    : "l"(da), "l"(db), "r"(scale_d), "n"(TA), "n"(TB));
}
template<int TA, int TB> __device__ __forceinline__ void wgmma_ss_n64(float (&d)[32], uint64_t da, uint64_t db, int scale_d) {
  asm volatile("{\n.reg .pred p;\nsetp.ne.b32 p, %34, 0;\nwgmma.mma_async.sync.aligned.m64n64k16.f32.bf16.bf16 {%0,%1,%2,%3,%4,%5,%6,%7,%8,%9,%10,%11,%12,%13,%14,%15,%16,%17,%18,%19,%20,%21,%22,%23,%24,%25,%26,%27,%28,%29,%30,%31}, %32, %33, p, 1, 1, %35, %36;\n}"
    : "+f"(d[0]), "+f"(d[1]), "+f"(d[2]), "+f"(d[3]), "+f"(d[4]), "+f"(d[5]), "+f"(d[6]), "+f"(d[7]), "+f"(d[8]), "+f"(d[9]), "+f"(d[10]), "+f"(d[11]), "+f"(d[12]), "+f"(d[13]), "+f"(d[14]), "+f"(d[15]), "+f"(d[16]), "+f"(d[17]), "+f"(d[18]), "+f"(d[19]), "+f"(d[20]), "+f"(d[21]), "+f"(d[22]), "+f"(d[23]), "+f"(d[24]), "+f"(d[25]), "+f"(d[26]), "+f"(d[27]), "+f"(d[28]), "+f"(d[29]), "+f"(d[30]), "+f"(d[31])
    : "l"(da), "l"(db), "r"(scale_d), "n"(TA), "n"(TB));
}
template<int TA, int TB> __device__ __forceinline__ void wgmma_ss_n96(float (&d)[48], uint64_t da, uint64_t db, int scale_d) {
  asm volatile("{\n.reg .pred p;\nsetp.ne.b32 p, %50, 0;\nwgmma.mma_async.sync.aligned.m64n96k16.f32.bf16.bf16 {%0,%1,%2,%3,%4,%5,%6,%7,%8,%9,%10,%11,%12,%13,%14,%15,%16,%17,%18,%19,%20,%21,%22,%23,%24,%25,%26,%27,%28,%29,%30,%31,%32,%33,%34,%35,%36,%37,%38,%39,%40,%41,%42,%43,%44,%45,%46,%47}, %48, %49, p, 1, 1, %51, %52;\n}"
    : "+f"(d[0]), "+f"(d[1]), "+f"(d[2]), "+f"(d[3]), "+f"(d[4]), "+f"(d[5]), "+f"(d[6]), "+f"(d[7]), "+f"(d[8]), "+f"(d[9]), "+f"(d[10]), "+f"(d[11]), "+f"(d[12]), "+f"(d[13]), "+f"(d[14]), "+f"(d[15]), "+f"(d[16]), "+f"(d[17]), "+f"(d[18]), "+f"(d[19]), "+f"(d[20]), "+f"(d[21]), "+f"(d[22]), "+f"(d[23]), "+f"(d[24]), "+f"(d[25]), "+f"(d[26]), "+f"(d[27]), "+f"(d[28]), "+f"(d[29]), "+f"(d[30]), "+f"(d[31]), "+f"(d[32]), "+f"(d[33]), "+f"(d[34]), "+f"(d[35]), "+f"(d[36]), "+f"(d[37]), "+f"(d[38]), "+f"(d[39]), "+f"(d[40]), "+f"(d[41]), "+f"(d[42]), "+f"(d[43]), "+f"(d[44]), "+f"(d[45]), "+f"(d[46]), "+f"(d[47])
    : "l"(da), "l"(db), "r"(scale_d), "n"(TA), "n"(TB));
}
template<int TA, int TB> __device__ __forceinline__ void wgmma_ss_n128(float (&d)[64], uint64_t da, uint64_t db, int scale_d) {
  asm volatile("{\n.reg .pred p;\nsetp.ne.b32 p, %66, 0;\nwgmma.mma_async.sync.aligned.m64n128k16.f32.bf16.bf16 {%0,%1,%2,%3,%4,%5,%6,%7,%8,%9,%10,%11,%12,%13,%14,%15,%16,%17,%18,%19,%20,%21,%22,%23,%24,%25,%26,%27,%28,%29,%30,%31,%32,%33,%34,%35,%36,%37,%38,%39,%40,%41,%42,%43,%44,%45,%46,%47,%48,%49,%50,%51,%52,%53,%54,%55,%56,%57,%58,%59,%60,%61,%62,%63}, %64, %65, p, 1, 1, %67, %68;\n}"
    : "+f"(d[0]), "+f"(d[1]), "+f"(d[2]), "+f"(d[3]), "+f"(d[4]), "+f"(d[5]), "+f"(d[6]), "+f"(d[7]), "+f"(d[8]), "+f"(d[9]), "+f"(d[10]), "+f"(d[11]), "+f"(d[12]), "+f"(d[13]), "+f"(d[14]), "+f"(d[15]), "+f"(d[16]), "+f"(d[17]), "+f"(d[18]), "+f"(d[19]), "+f"(d[20]), "+f"(d[21]), "+f"(d[22]), "+f"(d[23]), "+f"(d[24]), "+f"(d[25]), "+f"(d[26]), "+f"(d[27]), "+f"(d[28]), "+f"(d[29]), "+f"(d[30]), "+f"(d[31]), "+f"(d[32]), "+f"(d[33]), "+f"(d[34]), "+f"(d[35]), "+f"(d[36]), "+f"(d[37]), "+f"(d[38]), "+f"(d[39]), "+f"(d[40]), "+f"(d[41]), "+f"(d[42]), "+f"(d[43]), "+f"(d[44]), "+f"(d[45]), "+f"(d[46]), "+f"(d[47]), "+f"(d[48]), "+f"(d[49]), "+f"(d[50]), "+f"(d[51]), "+f"(d[52]), "+f"(d[53]), "+f"(d[54]), "+f"(d[55]), "+f"(d[56]), "+f"(d[57]), "+f"(d[58]), "+f"(d[59]), "+f"(d[60]), "+f"(d[61]), "+f"(d[62]), "+f"(d[63])
    : "l"(da), "l"(db), "r"(scale_d), "n"(TA), "n"(TB));
}

__device__ __forceinline__ uint64_t mkdesc(uint32_t lo, uint32_t hi) { uint64_t d; asm("mov.b64 %0, {%1, %2};" : "=l"(d) : "r"(lo), "r"(hi)); return d; }
__device__ __forceinline__ void mbar_init(uint32_t a, int c) { asm volatile("mbarrier.init.shared::cta.b64 [%0], %1;" :: "r"(a), "r"(c)); }
__device__ __forceinline__ void mbar_expect(uint32_t a, uint32_t b) { asm volatile("mbarrier.arrive.expect_tx.shared::cta.b64 _, [%0], %1;" :: "r"(a), "r"(b) : "memory"); }
__device__ __forceinline__ void mbar_arrive(uint32_t a) { asm volatile("mbarrier.arrive.shared::cta.b64 _, [%0];" :: "r"(a) : "memory"); }
#define SPIN_LIMIT (1 << 20)
#define SPIN_FAIL(code) __trap()
__device__ __forceinline__ void mbar_wait(uint32_t a, uint32_t ph) {
    asm volatile("{\n.reg .pred p, q;\n.reg .u32 c;\nmov.u32 c, 0;\n"
                 "W0:\nmbarrier.try_wait.parity.shared::cta.b64 p, [%0], %1;\n@p bra W1;\n"
                 "add.u32 c, c, 1;\nsetp.lt.u32 q, c, %2;\n@q bra W0;\ntrap;\n"
                 "W1:\n}" :: "r"(a), "r"(ph), "n"(4 * SPIN_LIMIT) : "memory");
}
__device__ __forceinline__ void mbar_sleep(uint32_t a, uint32_t ph) {
    asm volatile("{\n.reg .pred p, q;\n.reg .u32 c;\nmov.u32 c, 0;\n"
                 "W0:\nmbarrier.try_wait.parity.shared::cta.b64 p, [%0], %1, 4000;\n@p bra W1;\n"
                 "add.u32 c, c, 1;\nsetp.lt.u32 q, c, %2;\n@q bra W0;\ntrap;\n"
                 "W1:\n}" :: "r"(a), "r"(ph), "n"(SPIN_LIMIT) : "memory");
}
__device__ __forceinline__ void wg_fence() { asm volatile("wgmma.fence.sync.aligned;" ::: "memory"); }
__device__ __forceinline__ void wg_commit() { asm volatile("wgmma.commit_group.sync.aligned;" ::: "memory"); }
template<int N> __device__ __forceinline__ void wg_wait() { asm volatile("wgmma.wait_group.sync.aligned %0;" :: "n"(N) : "memory"); }
__device__ __forceinline__ void bar_sync(int id, int n) { asm volatile("bar.sync %0, %1;" :: "r"(id), "r"(n) : "memory"); }
__device__ __forceinline__ void bar_arrive(int id, int n) { asm volatile("bar.arrive %0, %1;" :: "r"(id), "r"(n) : "memory"); }
__device__ __forceinline__ void fence_async() { asm volatile("fence.proxy.async.global;" ::: "memory"); }
__device__ __forceinline__ void flag_wait(int f, unsigned target) {
    const unsigned* p = &g_flags[f * 8];
    unsigned v;
    #pragma unroll 1
    for (int it = 0; it < SPIN_LIMIT; it++) {
        asm volatile("ld.acquire.gpu.global.u32 %0, [%1];" : "=r"(v) : "l"(p) : "memory");
        if (v >= target) return;
        __nanosleep(20);
    }
    SPIN_FAIL(f);
}
__device__ __forceinline__ void flag_add(int f) { asm volatile("red.release.gpu.global.add.u32 [%0], 1;" :: "l"(&g_flags[f * 8]) : "memory"); }
__device__ __forceinline__ void tma2d(uint32_t dst, const CUtensorMap* m, int c0, int c1, uint32_t bar) {
    asm volatile("cp.async.bulk.tensor.2d.shared::cluster.global.mbarrier::complete_tx::bytes [%0], [%1, {%3, %4}], [%2];"
        :: "r"(dst), "l"(m), "r"(bar), "r"(c0), "r"(c1) : "memory");
}
__device__ __forceinline__ void bulk_ld(uint32_t dst, const void* src, uint32_t bytes, uint32_t bar) {
    asm volatile("cp.async.bulk.shared::cluster.global.mbarrier::complete_tx::bytes [%0], [%1], %2, [%3];"
        :: "r"(dst), "l"(src), "r"(bytes), "r"(bar) : "memory");
}
__device__ __forceinline__ void tma3d_mc(uint32_t dst, const CUtensorMap* m, int c1, int c2, uint32_t bar) {
    asm volatile("cp.async.bulk.tensor.3d.shared::cluster.global.mbarrier::complete_tx::bytes.multicast::cluster [%0], [%1, {0, %3, %4}], [%2], %5;"
        :: "r"(dst), "l"(m), "r"(bar), "r"(c1), "r"(c2), "h"((uint16_t)3) : "memory");
}
__device__ __forceinline__ void bulk_ld_mc(uint32_t dst, const void* src, uint32_t bytes, uint32_t bar) {
    asm volatile("cp.async.bulk.shared::cluster.global.mbarrier::complete_tx::bytes.multicast::cluster [%0], [%1], %2, [%3], %4;"
        :: "r"(dst), "l"(src), "r"(bytes), "r"(bar), "h"((uint16_t)3) : "memory");
}
__device__ __forceinline__ void release2(uint32_t a, uint32_t peer_off) {
    asm volatile("mbarrier.arrive.shared::cta.b64 _, [%0];\nmbarrier.arrive.shared::cluster.b64 _, [%1];" :: "r"(a), "r"(a + peer_off) : "memory");
}
__device__ __forceinline__ void release2n(uint32_t a, uint32_t pa, uint32_t cnt) {
    asm volatile("{\n.reg .pred p;\nsetp.ne.u32 p, %2, 0;\n@p mbarrier.arrive.shared::cta.b64 _, [%0], %2;\n@p mbarrier.arrive.shared::cluster.b64 _, [%1], %2;\n}"
                 :: "r"(a), "r"(pa), "r"(cnt) : "memory");
}
__device__ __forceinline__ bool elect_one() {
    uint32_t p;
    asm volatile("{\n.reg .pred q;\nelect.sync _|q, 0xffffffff;\nselp.u32 %0, 1, 0, q;\n}" : "=r"(p));
    return p != 0;
}
__device__ __forceinline__ void l2_prefetch(const void* src, uint32_t bytes) {
    asm volatile("cp.async.bulk.prefetch.L2.global [%0], %1;" :: "l"(src), "r"(bytes) : "memory");
}
__device__ __forceinline__ uint32_t pack_bf16(float lo, float hi) { uint32_t r; asm("cvt.rn.bf16x2.f32 %0, %1, %2;" : "=r"(r) : "f"(hi), "f"(lo)); return r; }
__device__ __forceinline__ float bf_lo(uint32_t v) { return __uint_as_float(v << 16); }
__device__ __forceinline__ float bf_hi(uint32_t v) { return __uint_as_float(v & 0xFFFF0000u); }
__device__ __forceinline__ float gelu2_tanh(float x) {
    float u = x * fmaf(x * x, 0.0356774081363001f, 0.7978845608028654f), t;
    asm("tanh.approx.f32 %0, %1;" : "=f"(t) : "f"(u));
    return fmaf(x, t, x);
}
#define FENCE_F(a, n) _Pragma("unroll") for (int i_ = 0; i_ < n; i_++) asm volatile("" : "+f"(a[i_]) :: "memory");
#define FENCE_R(a, n) _Pragma("unroll") for (int i_ = 0; i_ < n; i_++) asm volatile("" : "+r"(a[i_]) :: "memory");

__device__ __forceinline__ uint32_t exp2_mufu(float a, float b) {
    float x, y;
    asm("ex2.approx.ftz.f32 %0, %1;" : "=f"(x) : "f"(a));
    asm("ex2.approx.ftz.f32 %0, %1;" : "=f"(y) : "f"(b));
    return pack_bf16(x, y);
}
__device__ __forceinline__ uint32_t exp2_alu(float a, float b, uint32_t half2c) {
    uint32_t L = __byte_perm(__float_as_uint(a), __float_as_uint(b), 0x6521), G, E, r;
    asm("lop3.b32 %0, %1, 0x007F007F, %2, 0xE2;" : "=r"(G) : "r"(L), "r"(half2c));
    asm("lop3.b32 %0, %1, 0x007F007F, %2, 0xB8;" : "=r"(E) : "r"(L), "r"(half2c));
    asm("fma.rn.bf16x2 %0, %1, %2, %3;" : "=r"(r) : "r"(G), "r"(L), "r"(E));
    return r;
}
#define EXPBLK(p, s) _Pragma("unroll") for (int b = 0; b < 8; b++) { \
    if ((PAT >> b) & 1) { p[2*b] = exp2_alu(s[4*b], s[4*b+1], half2c); p[2*b+1] = exp2_alu(s[4*b+2], s[4*b+3], half2c); } \
    else { p[2*b] = exp2_mufu(s[4*b], s[4*b+1]); p[2*b+1] = exp2_mufu(s[4*b+2], s[4*b+3]); } }

struct Ring { uint32_t st, ph; };
template<int NST> __device__ __forceinline__ void ring_next(Ring& r) { if (++r.st == NST) { r.st = 0; r.ph ^= 1; } }

struct OpDesc { uint32_t lo, hi, step, step2, nsplit; };

template<int N, int PART> __device__ __forceinline__ void wgmma_ss(float (&d)[N / 2], uint64_t da, uint64_t db, int sc) {
    if constexpr (N == 160) {
        if constexpr (PART == 0) wgmma_ss_n96<0, 1>(*(float(*)[48])&d[0], da, db, sc);
        else wgmma_ss_n64<0, 1>(*(float(*)[32])&d[48], da, db, sc);
    } else if constexpr (N == 192) {
        if constexpr (PART == 0) wgmma_ss_n128<0, 1>(*(float(*)[64])&d[0], da, db, sc);
        else wgmma_ss_n64<0, 1>(*(float(*)[32])&d[64], da, db, sc);
    } else {
        if constexpr (PART == 0) wgmma_ss_n128<0, 1>(*(float(*)[64])&d[0], da, db, sc);
        else wgmma_ss_n96<0, 1>(*(float(*)[48])&d[64], da, db, sc);
    }
}

struct GemmCtx { Ring r; uint32_t sb16, bar_full, bar_empty, peer_off; bool lead; };

template<int N, int NS, int GB>
__device__ __forceinline__ void gemm_loop(float (&acc)[N / 2], int nkb, int first, OpDesc a, OpDesc b, GemmCtx& c) {
    uint32_t prev = 0;
    #pragma unroll 1
    for (int kb = 0; kb < nkb; kb++) {
        mbar_sleep(c.bar_full + 8 * c.r.st, c.r.ph);
        const uint32_t base = c.sb16 + c.r.st * (GST_BYTES / 16);
        const uint64_t da0 = mkdesc(base + a.lo, a.hi), db0 = mkdesc(base + b.lo, b.hi);
        wg_fence();
        #pragma unroll
        for (int k = 0; k < NS; k++) {
            const uint64_t da = da0 + k * a.step, db = db0 + ((k & 1) * b.step + (k >> 1) * b.step2);
            const int sc = (k > 0) | (kb > 0) | !first;
            wgmma_ss<N, 0>(acc, da, db, sc);
            if constexpr (GB > 0) { wg_commit(); wg_wait<GB - 1>(); }
            wgmma_ss<N, 1>(acc, da, db + b.nsplit, sc);
            if constexpr (GB < 0) {
                if ((k + 1) % (-GB) == 0 || k == NS - 1) {
                    wg_commit(); wg_wait<1>();
                    if (k < -GB && kb > 0 && c.lead) release2(c.bar_empty + 8 * prev, c.peer_off);
                }
            }
            if constexpr (GB > 0) {
                wg_commit(); wg_wait<GB - 1>();
                if (k == (GB - 1) / 2 && kb > 0 && c.lead) release2(c.bar_empty + 8 * prev, c.peer_off);
            }
        }
        if constexpr (GB == 0) {
            wg_commit();
            wg_wait<1>();
            if (kb > 0 && c.lead) release2(c.bar_empty + 8 * prev, c.peer_off);
        }
        prev = c.r.st;
        ring_next<GST>(c.r);
    }
    wg_wait<0>();
    if (c.lead) release2(c.bar_empty + 8 * prev, c.peer_off);
    FENCE_F(acc, N / 2);
}

template<int CNT, int SUBS>
__device__ __forceinline__ void retile_ld(uint4 (&v)[CNT], const __nv_bfloat16* src, int pitch, int ncg, int nkg, int cm0, int cnt, int id) {
    const int sub = id >> 3, row = id & 7;
    #pragma unroll
    for (int i = 0; i < CNT; i++) {
        const int l = sub + i * SUBS, cm = cm0 + l, kg = cm / ncg, cg = cm - kg * ncg;
        if (l < cnt && kg < nkg) v[i] = __ldg((const uint4*)(src + (size_t)(kg * 8 + row) * pitch + cg * 8));
    }
}
template<int NG, int CNT, int SUBS, bool PERM>
__device__ __forceinline__ void retile_st(const uint4 (&v)[CNT], int ncg, int nkg, uint8_t* dst, int cm0, int cnt, int id) {
    const int sub = id >> 3, row = id & 7;
    #pragma unroll
    for (int i = 0; i < CNT; i++) {
        const int l = sub + i * SUBS, cm = cm0 + l, kg = cm / ncg, cg = cm - kg * ncg, tile = cg / NG;
        int kd = kg;
        if (PERM) { const int q = kg / 20, rem = kg - q * 20; kd = rem < 4 ? q * 4 + rem : (rem < 12 ? 12 + q * 8 + rem : 36 + q * 8 + rem); }
        if (l < cnt && kg < nkg) *(uint4*)(dst + (size_t)((tile * nkg + kd) * NG + (cg - tile * NG)) * 128 + row * 16) = v[i];
    }
}

__global__ void __cluster_dims__(2, 1, 1) __launch_bounds__(640, 1) mega_kernel(const __grid_constant__ Params p) {
    extern __shared__ uint8_t smem_raw[];
    const uint32_t sb = ((uint32_t)__cvta_generic_to_shared(smem_raw) + 1023u) & ~1023u;
    uint8_t* sm = smem_raw + (sb - (uint32_t)__cvta_generic_to_shared(smem_raw));
    const uint32_t bar_gfull = sb + SM_MISC, bar_gempty = bar_gfull + 64, bar_kfull = bar_gfull + 128, bar_kempty = bar_gfull + 192;
    float* s_gate = (float*)(sm + SM_MISC + 256);
    float* s_stat = (float*)(sm + SM_MISC + 512);
    float* s_red = (float*)(sm + SM_MISC + 768);
    const int rb = blockIdx.x & 31, ct = blockIdx.x >> 5;
    const int rank = rb & 1;
    const int wg = __shfl_sync(0xffffffffu, threadIdx.x >> 7, 0);
    const int tid = threadIdx.x & 127, w = tid >> 5, lane = tid & 31, g = lane >> 2, t = lane & 3;
    uint32_t peer_off;
    asm("mapa.shared::cluster.u32 %0, %1, %2;" : "=r"(peer_off) : "r"(sb), "r"(rank ^ 1));
    peer_off -= sb;

    if (threadIdx.x >= 576 && threadIdx.x < 580) asm volatile("prefetch.tensormap [%0];" :: "l"(&p.mx + (threadIdx.x - 576)) : "memory");
    if (threadIdx.x == 544) {
        l2_prefetch(p.wq + (size_t)blockIdx.x * 3200, 6400);
        l2_prefetch(p.win + (size_t)blockIdx.x * 8640, 17280);
    }
    if (__shfl_sync(0xffffffffu, threadIdx.x >> 5, 0) == 16 && elect_one()) {
        for (int i = 0; i < GST; i++) { mbar_init(bar_gfull + 8 * i, 1); mbar_init(bar_gempty + 8 * i, 8); }
        for (int i = 0; i < KST; i++) { mbar_init(bar_kfull + 8 * i, 1); mbar_init(bar_kempty + 8 * i, 24); }
        mbar_init(bar_kfull + 32, 1); mbar_init(bar_kfull + 40, 1); mbar_init(bar_kfull + 48, 1);
        asm volatile("fence.mbarrier_init.release.cluster;" ::: "memory");
        asm volatile("fence.proxy.async.shared::cta;" ::: "memory");
        if (ct == 3) {
            mbar_arrive(bar_gfull + 24);
            mbar_expect(bar_kfull + 48, 2 * 25600 + 1280);
            bulk_ld(sb + SM_W, p.wk, 25600, bar_kfull + 48);
            bulk_ld(sb + SM_W + 25600, p.wv, 25600, bar_kfull + 48);
            bulk_ld(sb + SM_W + 51200, p.gw, 1280, bar_kfull + 48);
            #pragma unroll 1
            for (int kb = 0; kb < 10; kb++) {
                if ((kb & 3) == 0) mbar_expect(bar_gfull + (kb >> 2) * 8, kb < 8 ? 32768 : 16384);
                tma2d(sb + SM_G + (kb >> 2) * GST_BYTES + (kb & 3) * 8192, &p.mx, kb * 64, rb * 64, bar_gfull + (kb >> 2) * 8);
            }
        }
    }
    asm volatile("barrier.cluster.arrive.relaxed;\nbarrier.cluster.wait.acquire;" ::: "memory");

    if (wg == 4) {
        asm volatile("setmaxnreg.dec.sync.aligned.u32 24;");
        const int wu = __shfl_sync(0xffffffffu, w, 0);
        static_assert(GST == 4, "ring indices are derived from a running stage counter");
        #define STG_ADDR(n) (sb + SM_G + ((n) & 3) * GST_BYTES)
        #define STG_FULL(n) (bar_gfull + ((n) & 3) * 8)
        #define STG_WAIT(n) mbar_sleep(bar_gempty + ((n) & 3) * 8, (((n) >> 2) & 1) ^ 1)
        const uint32_t n0 = ct == 3 ? 4 : 0;
        if (wu == 0) {
            uint32_t n = n0;
            if (elect_one()) {
                #pragma unroll 1
                for (int kb = 0; kb < 10; kb++, n++) {
                    STG_WAIT(n);
                    mbar_expect(STG_FULL(n), 8192 + 20480);
                    tma3d_mc(STG_ADDR(n) + 8192 + rank * 10240, &p.mwq, kb * 64 + rank * 32, 5 * ct, STG_FULL(n));
                }
                #pragma unroll 1
                for (int i = 0; i < 20; i++, n++) {
                    STG_WAIT(n);
                    mbar_expect(STG_FULL(n), 8192 + 28672);
                    tma3d_mc(STG_ADDR(n) + 8192 + rank * 14336, &p.mwin, (i < 10 ? i : i - 10) * 64 + rank * 32, (i < 10 ? 27 : 0) + 7 * ct, STG_FULL(n));
                }
            }
            __syncwarp();
            #pragma unroll 1
            for (int it = 0; ; it++) {
                unsigned v;
                asm volatile("ld.acquire.gpu.global.u32 %0, [%1];" : "=r"(v) : "l"(&g_flags[(F_Z2 + lane * 4 + ct) * 8]) : "memory");
                if (__all_sync(0xffffffffu, v != 0)) break;
                if (it > SPIN_LIMIT) SPIN_FAIL(F_Z2);
                __nanosleep(20);
            }
            if (elect_one()) {
                n = n0 + 30;
                fence_async();
                const uint8_t* src = g_z2n + (size_t)ct * 32 * 28672 + rank * 14336;
                #pragma unroll 1
                for (int kb = 0; kb < 32; kb++, n++, src += 28672) {
                    STG_WAIT(n);
                    mbar_expect(STG_FULL(n), 8192 + 28672);
                    bulk_ld_mc(STG_ADDR(n) + 8192 + rank * 14336, src, 14336, STG_FULL(n));
                }
                flag_wait(F_WR, 96);
                fence_async();
                n++;
                #pragma unroll 1
                for (int i = 0; i < 2; i++, n++) {
                    STG_WAIT(n);
                    mbar_expect(STG_FULL(n), 28672);
                    bulk_ld_mc(STG_ADDR(n) + 8192 + rank * 10240, g_wot + (size_t)(ct * 80 + i * 8) * 2560 + rank * 10240, 10240, STG_FULL(n));
                }
                uint32_t k0 = 28 * ct + rank * 4;
                #pragma unroll 1
                for (int i = 0; i < 14; i++, n++) {
                    const uint32_t nk = i == 13 ? 2 : 4;
                    if (i == 13) k0 -= rank * 2;
                    if (k0 >= 108) k0 -= 108;
                    STG_WAIT(n);
                    mbar_expect(STG_FULL(n), nk * 2 * (2560 + 1024));
                    bulk_ld_mc(STG_ADDR(n) + 8192 + rank * nk * 2560, g_woutt + (size_t)(ct * 108 + k0) * 2560, nk * 2560, STG_FULL(n));
                    k0 += 8;
                }
                #pragma unroll 1
                for (int i = 2; i < 10; i++, n++) {
                    STG_WAIT(n);
                    mbar_expect(STG_FULL(n), 28672);
                    bulk_ld_mc(STG_ADDR(n) + 8192 + rank * 10240, g_wot + (size_t)(ct * 80 + i * 8) * 2560 + rank * 10240, 10240, STG_FULL(n));
                }
            }
        } else if (wu == 3) {
            if (elect_one()) {
                uint32_t n = n0;
                #pragma unroll 1
                for (int j = 0; j < 3; j++) {
                    #pragma unroll 1
                    for (int kb = 0; kb < 10; kb++, n++) {
                        STG_WAIT(n);
                        tma2d(STG_ADDR(n), &p.mx, kb * 64, rb * 64, STG_FULL(n));
                        if (j > 0 && kb >= 2) l2_prefetch(p.wsp + (size_t)(rb * 64 + ct * 16 + (j - 1) * 8 + kb - 2) * S_LEN, 4096);
                    }
                }
                #define STASH_STAGE(which) { STG_WAIT(n); fence_async(); mbar_expect(STG_FULL(n), 28672); \
                    bulk_ld(STG_ADDR(n), g_z1 + (size_t)((which) * NCTA + blockIdx.x) * 1792, 28672, STG_FULL(n)); n++; }
                #pragma unroll 1
                for (int kb = 0; kb < 32; kb++, n++) {
                    STG_WAIT(n);
                    tma2d(STG_ADDR(n), &p.mwsp, kb * 64, rb * 64, STG_FULL(n));
                }
                STASH_STAGE(0)
                const uint8_t* op = g_op + (size_t)rb * 80 * 1024;
                const uint8_t* hp = g_hp + (size_t)rb * 108 * 1024;
                flag_wait(F_O + rb * 3, 4);
                fence_async();
                #pragma unroll 1
                for (int i = 0; i < 2; i++, n++) { STG_WAIT(n); bulk_ld(STG_ADDR(n), op + i * 8192, 8192, STG_FULL(n)); }
                mbar_sleep(bar_kfull + 40, 0);
                fence_async();
                uint32_t k0 = 28 * ct;
                #pragma unroll 1
                for (int i = 0; i < 14; i++, n++) {
                    if (i == 3) { flag_wait(F_H + rb, 4); fence_async(); }
                    STG_WAIT(n);
                    const uint32_t nb = (i == 13 || k0 == 104) ? 4096 : 8192;
                    bulk_ld(STG_ADDR(n), hp + k0 * 1024, nb, STG_FULL(n));
                    if (k0 == 104 && i != 13) bulk_ld(STG_ADDR(n) + 4096, hp, 4096, STG_FULL(n));
                    k0 += 8; if (k0 >= 108) k0 -= 108;
                }
                #pragma unroll 1
                for (int i = 2; i < 10; i++, n++) {
                    if (i == 2 || i == 6) { flag_wait(F_O + rb * 3 + (i == 2 ? 1 : 2), i == 2 ? 4 : 12); fence_async(); }
                    STG_WAIT(n);
                    bulk_ld(STG_ADDR(n), op + i * 8192, 8192, STG_FULL(n));
                }
            }
            __syncwarp();
            unsigned d = 0;
            if (lane == 0) d = atomicAdd(&g_flags[F_DONE * 8], 1u);
            if (__shfl_sync(0xffffffffu, d, 0) == NCTA - 1) {
                #pragma unroll
                for (int i = 0; i < (F_NUM + 31) / 32; i++) if (i * 32 + lane < F_NUM) g_flags[(i * 32 + lane) * 8] = 0;
            }
        } else if (wu == 1) {
            if (elect_one()) {
                flag_wait(F_KV, 32);
                asm volatile("fence.proxy.async.global;" ::: "memory");
                mbar_expect(bar_kfull + 32, 3072 + 512);
                bulk_ld(sb + SM_KV + 3 * KST_BYTES + 6144, g_kv + 31 * 6144, 3072, bar_kfull + 32);
                bulk_ld(sb + SM_MISC + 512, g_kvmax, 256, bar_kfull + 32);
                bulk_ld(sb + SM_MISC + 256, g_gate + rb * 64, 256, bar_kfull + 32);
                #pragma unroll 1
                for (int i = 0; i < 48; i++) {
                    const uint32_t st = i & 3;
                    if (i >= 3) mbar_sleep(bar_kempty + 8 * st, (((i + 1) >> 2) & 1) ^ 1);
                    mbar_expect(bar_kfull + 8 * st, KST_BYTES);
                    bulk_ld_mc(sb + SM_KV + st * KST_BYTES + rank * 6144, g_kv + (i & 15) * KST_BYTES + rank * 6144, 6144, bar_kfull + 8 * st);
                    if (i == 19 || i == 35) flag_add(F_O + rb * 3 + (i == 35));
                }
            }
        } else {
            if (ct == 3) {
                bar_sync(10, 160);
                if (lane < 2) {
                    const float* r = s_red + 8 + 4 * lane;
                    g_kvmax[lane * 32 + rb] = __uint_as_float(max(max(__float_as_uint(r[0]), __float_as_uint(r[1])), max(__float_as_uint(r[2]), __float_as_uint(r[3]))));
                }
                __syncwarp();
                if (elect_one()) flag_add(F_KV);
                __syncwarp();
            }
            bar_sync(10, 160);
            if (elect_one()) { flag_add(F_H + rb); mbar_arrive(bar_kfull + 40); }
        }
    } else if (wg == 3) {
        asm volatile("setmaxnreg.inc.sync.aligned.u32 144;");
        GemmCtx c{{0, 0}, ((sb + SM_G) & 0x3FFFFu) >> 4, bar_gfull, bar_gempty, peer_off, lane == 0};
        const OpDesc a_sw{0u, 64u | (1u << 30), 2u, 0u, 0u};
        const OpDesc a_t{64u << 16, 8u, 128u, 0u, 0u};
        const OpDesc b_q{512u | (128u << 16), 32u | (2u << 30), 64u, 640u, 384u};
        const OpDesc b_w{512u | (128u << 16), 32u | (2u << 30), 64u, 896u, 512u};
        const OpDesc b_z{512u | (224u << 16), 8u, 448u, 896u, 128u};
        const OpDesc b_o{512u | (160u << 16), 8u, 320u, 640u, 96u};
        const int r0 = 16 * w + g;
        if (ct == 3) {
            float ex[24];
            const uint32_t exlo = (((sb + SM_KV) & 0x3FFFFu) >> 4) | (48u << 16);
            bar_sync(1, 512);
            #pragma unroll 1
            for (int kb = 0; kb < 10; kb++) {
                if ((kb & 3) == 0) mbar_wait(bar_gfull + 8 * (kb >> 2), 0);
                const uint32_t base = c.sb16 + (kb >> 2) * (GST_BYTES / 16) + (kb & 3) * 512;
                wg_fence();
                #pragma unroll
                for (int k = 0; k < 4; k++) wgmma_ss_n48<0, 1>(ex, mkdesc(base + 2 * k, a_sw.hi), mkdesc(exlo + (kb * 4 + k) * 96, 8), (k > 0) | (kb > 0));
                wg_commit();
            }
            wg_wait<0>();
            FENCE_F(ex, 24);
            if (lane < 4) release2(bar_gempty + 8 * lane, peer_off);
            c.r.ph = 1;
            uint8_t* dk = g_kv + ((rb + 31) & 31) * 6144 + 2 * w * 384 + g * 16 + t * 4;
            uint8_t* dv = g_kv + rb * 6144 + 3072 + 2 * w * 384 + g * 16 + t * 4;
            uint32_t mk = 0, mv = 0;
            #pragma unroll
            for (int hi = 0; hi < 2; hi++) {
                const bool alu = (PAT >> (2 * w + hi)) & 1;
                float n2 = 0.f;
                #pragma unroll
                for (int j = 0; j < 3; j++) {
                    uint32_t v = pack_bf16(ex[4 * j + 2 * hi], ex[4 * j + 2 * hi + 1]);
                    const float a = bf_lo(v), b = bf_hi(v);
                    n2 = fmaf(a, a, fmaf(b, b, n2));
                    if (alu) v = pack_bf16(2.f * a, 2.f * b);
                    if (j == 2 && t == 2) v = alu ? 0x3C004440u : 0xBAF03FCCu;
                    *(uint32_t*)(dk + hi * 384 + j * 128) = v;
                    v = pack_bf16(ex[12 + 4 * j + 2 * hi], ex[12 + 4 * j + 2 * hi + 1]);
                    if (j < 2 || t < 2) mv = max(mv, max((v << 16) & 0x7FFF0000u, v & 0x7FFF0000u));
                    if (j == 2 && t == 3) {
                        g_gate[rb * 64 + r0 + 8 * hi] = 1.f / (1.f + __expf(-ex[20 + 2 * hi]));
                        v = 0u;
                    }
                    if (j == 2 && t == 2) v = 0x00003F80u;
                    *(uint32_t*)(dv + hi * 384 + j * 128) = v;
                }
                n2 += __shfl_xor_sync(0xffffffffu, n2, 1); n2 += __shfl_xor_sync(0xffffffffu, n2, 2);
                mk = max(mk, __float_as_uint(n2) & 0x7FFFFFFFu);
            }
            mk = __reduce_max_sync(0xffffffffu, mk); mv = __reduce_max_sync(0xffffffffu, mv);
            if (lane == 0) { s_red[8 + w] = __uint_as_float(mk); s_red[12 + w] = __uint_as_float(mv); }
            bar_arrive(10, 160);
        }
        {
            float acc[80];
            gemm_loop<160, 4, 0>(acc, 10, 1, a_sw, b_q, c);
            uint8_t* qs = sm + SM_Q + 2 * w * 128 + g * 16;
            #pragma unroll
            for (int j = 0; j < 20; j++) {
                constexpr int dummy = 0; (void)dummy;
                const int h0 = (8 * j) / 20, d0 = (8 * j) % 20, d = d0 + 2 * t;
                const int off = d < 20 ? h0 * 3072 + (d >> 3) * 1024 + (d & 7) * 2 : (h0 + 1) * 3072 + (d - 20) * 2;
                *(uint32_t*)(qs + off) = pack_bf16(acc[4 * j] * 0.3225964182229561f, acc[4 * j + 1] * 0.3225964182229561f);
                *(uint32_t*)(qs + off + 128) = pack_bf16(acc[4 * j + 2] * 0.3225964182229561f, acc[4 * j + 3] * 0.3225964182229561f);
            }
            bar_arrive(2, 384);
            bar_arrive(13, 256);
        }
        {
            float acc[112];
            #pragma unroll
            for (int i = 96; i < 112; i++) acc[i] = 0.f;
            #define GEMM_Z(GBX, nkb, first, bd) { if (ct == 3) gemm_loop<192, 4, GBX>(*(float(*)[96])&acc[0], nkb, first, a_sw, bd, c); \
                                                  else gemm_loop<224, 4, GBX>(acc, nkb, first, a_sw, bd, c); }
            GEMM_Z(GB2, 10, 1, b_w)
            uint4* z1p = g_z1 + (size_t)blockIdx.x * 14 * 128 + tid;
            {
                float s0 = 0.f, q0 = 0.f, s1 = 0.f, q1 = 0.f;
                #pragma unroll
                for (int j = 0; j < 14; j++) {
                    float y[8];
                    #pragma unroll
                    for (int i = 0; i < 8; i++) y[i] = gelu2_tanh(acc[8 * j + i]);
                    s0 += (y[0] + y[1]) + (y[4] + y[5]); q0 = fmaf(y[0], y[0], fmaf(y[1], y[1], fmaf(y[4], y[4], fmaf(y[5], y[5], q0))));
                    s1 += (y[2] + y[3]) + (y[6] + y[7]); q1 = fmaf(y[2], y[2], fmaf(y[3], y[3], fmaf(y[6], y[6], fmaf(y[7], y[7], q1))));
                    z1p[(NCTA * 14 + j) * 128] = make_uint4(pack_bf16(y[0], y[1]), pack_bf16(y[2], y[3]), pack_bf16(y[4], y[5]), pack_bf16(y[6], y[7]));
                }
                #pragma unroll
                for (int o = 1; o <= 2; o <<= 1) {
                    s0 += __shfl_xor_sync(0xffffffffu, s0, o); q0 += __shfl_xor_sync(0xffffffffu, q0, o);
                    s1 += __shfl_xor_sync(0xffffffffu, s1, o); q1 += __shfl_xor_sync(0xffffffffu, q1, o);
                }
                if (t < 2) asm volatile("st.relaxed.gpu.global.b64 [%0], %1;" :: "l"(&g_part[(rb * 4 + ct) * 64 + r0 + 8 * t]),
                                        "l"(mkdesc(__float_as_uint(t ? s1 : s0), __float_as_uint(t ? q1 : q0) | 0x80000000u)) : "memory");
            }
            bar_arrive(11, 256);
            GEMM_Z(GB3, 10, 1, b_w)
            #pragma unroll
            for (int j = 0; j < 14; j++)
                z1p[j * 128] = make_uint4(pack_bf16(gelu2_tanh(acc[8 * j]), gelu2_tanh(acc[8 * j + 1])), pack_bf16(gelu2_tanh(acc[8 * j + 2]), gelu2_tanh(acc[8 * j + 3])),
                                          pack_bf16(gelu2_tanh(acc[8 * j + 4]), gelu2_tanh(acc[8 * j + 5])), pack_bf16(gelu2_tanh(acc[8 * j + 6]), gelu2_tanh(acc[8 * j + 7])));
            const float b0 = __bfloat162float(p.bsp[rb * 64 + r0]), b1 = __bfloat162float(p.bsp[rb * 64 + r0 + 8]);
            GEMM_Z(GB4, 32, 1, b_z)
            bar_sync(8, 512);
            const float g0 = 0.5f - 0.5f * s_gate[r0], g1 = 0.5f - 0.5f * s_gate[r0 + 8];
            {
                mbar_wait(c.bar_full + 8 * c.r.st, c.r.ph);
                const uint4* zs = (const uint4*)(sm + SM_G + c.r.st * GST_BYTES) + tid;
                uint8_t* dst = g_hp + (size_t)((rb * 108 + 28 * ct) * 8 + 2 * w) * 128 + g * 16 + t * 4;
                const float e0 = b0 * g0, e1 = b1 * g1;
                #pragma unroll
                for (int j = 0; j < 14; j++) {
                    if (j < 12 || ct < 3) {
                        const uint4 v = zs[j * 128];
                        *(uint32_t*)(dst + (2 * j) * 1024) = pack_bf16(fmaf(acc[8 * j], g0, e0) * bf_lo(v.x), fmaf(acc[8 * j + 1], g0, e0) * bf_hi(v.x));
                        *(uint32_t*)(dst + (2 * j) * 1024 + 128) = pack_bf16(fmaf(acc[8 * j + 2], g1, e1) * bf_lo(v.y), fmaf(acc[8 * j + 3], g1, e1) * bf_hi(v.y));
                        *(uint32_t*)(dst + (2 * j + 1) * 1024) = pack_bf16(fmaf(acc[8 * j + 4], g0, e0) * bf_lo(v.z), fmaf(acc[8 * j + 5], g0, e0) * bf_hi(v.z));
                        *(uint32_t*)(dst + (2 * j + 1) * 1024 + 128) = pack_bf16(fmaf(acc[8 * j + 6], g1, e1) * bf_lo(v.w), fmaf(acc[8 * j + 7], g1, e1) * bf_hi(v.w));
                    }
                }
                __syncwarp();
                if (c.lead) release2(c.bar_empty + 8 * c.r.st, c.peer_off);
                ring_next<GST>(c.r);
            }
            bar_arrive(10, 160);
        }
        {
            float acc[80];
            gemm_loop<160, 4, GB5>(acc, 15, 1, a_t, b_o, c);
            gemm_loop<160, 2, GB5>(acc, 1, 0, a_t, b_o, c);
            gemm_loop<160, 4, GB5>(acc, 4, 0, a_t, b_o, c);
            if (tid < 64) g_part[(rb * 4 + ct) * 64 + tid] = 0ull;
            gemm_loop<160, 4, 0>(acc, 4, 0, a_t, b_o, c);
            uint32_t* os = (uint32_t*)(sm + SM_Q) + r0 * (QS_PITCH / 2) + t;
            #pragma unroll
            for (int j = 0; j < 20; j++) {
                os[4 * j] = pack_bf16(acc[4 * j], acc[4 * j + 1]);
                os[8 * (QS_PITCH / 2) + 4 * j] = pack_bf16(acc[4 * j + 2], acc[4 * j + 3]);
            }
            asm volatile("fence.proxy.async.shared::cta;" ::: "memory");
            __syncwarp();
            if (lane < 16) {
                const int row = 16 * w + lane;
                asm volatile("cp.async.bulk.global.shared::cta.bulk_group [%0], [%1], 320;"
                             :: "l"(p.out + (size_t)(rb * 64 + row) * DM + 160 * ct), "r"(sb + SM_Q + row * (QS_PITCH * 2)) : "memory");
                asm volatile("cp.async.bulk.commit_group;\ncp.async.bulk.wait_group.read 0;" ::: "memory");
            }
            __syncwarp();
            asm volatile("barrier.cluster.arrive.relaxed;\nbarrier.cluster.wait;" ::: "memory");
        }
    } else {
        asm volatile("setmaxnreg.inc.sync.aligned.u32 104;");
        const int atid = threadIdx.x;
        {
            *(uint2*)(sm + SM_Q + 8 * 3072 + (atid & 127) * 8) = make_uint2(0u, 0u);
            if (ct < 3) {
                uint4 w1[2], w2[2];
                const int c1 = blockIdx.x * 67, c2 = blockIdx.x * 90;
                retile_ld<2, 48>(w1, p.wo, DM, 80, 80, c1, 67, atid);
                retile_ld<2, 48>(w2, p.wout, DM, 80, 108, c2, 90, atid);
                retile_st<20, 2, 48, true>(w1, 80, 80, g_wot, c1, 67, atid);
                retile_st<20, 2, 48, false>(w2, 80, 108, g_woutt, c2, 90, atid);
                bar_sync(9, 384);
                if (atid == 256) flag_add(F_WR);
            } else {
                mbar_wait(bar_kfull + 48, 0);
                #pragma unroll 2
                for (int e = atid; e < 1280; e += 384) {
                    const int m = e >= 640, k = e - m * 640;
                    const uint2* src = (const uint2*)(sm + SM_W + e * 40);
                    const uint2 a = src[0], b = src[1], c = src[2], d = src[3], f = src[4];
                    const uint32_t gt = m ? *(const unsigned short*)(sm + SM_W + 51200 + k * 2) : 0u;
                    uint4* dst = (uint4*)(sm + SM_KV + (k >> 3) * 768 + (k & 7) * 16 + m * 384);
                    dst[0] = make_uint4(a.x, a.y, b.x, b.y); dst[8] = make_uint4(c.x, c.y, d.x, d.y); dst[16] = make_uint4(f.x, f.y, 0u, gt);
                }
                asm volatile("fence.proxy.async.shared::cta;" ::: "memory");
                bar_arrive(1, 512);
            }
        }
        const uint32_t half2c = *(const volatile uint32_t*)&g_const[0];
        if (wg == 2) {
            const int r0 = 16 * w + g;
            uint4* z1p = g_z1 + (size_t)blockIdx.x * 14 * 128 + tid;
            uint4 v[14];
            bar_sync(11, 256);
            #pragma unroll
            for (int j = 0; j < 14; j++) v[j] = __ldcg(z1p + (NCTA * 14 + j) * 128);
            float s0, q0, s1, q1;
            {
                unsigned long long a, b;
                const unsigned long long* pa_ = &g_part[(rb * 4 + t) * 64 + r0];
                #pragma unroll 1
                for (int it = 0; ; it++) {
                    asm volatile("ld.relaxed.gpu.global.b64 %0, [%1];" : "=l"(a) : "l"(pa_) : "memory");
                    asm volatile("ld.relaxed.gpu.global.b64 %0, [%1];" : "=l"(b) : "l"(pa_ + 8) : "memory");
                    if (__all_sync(0xffffffffu, ((a & b) >> 63) != 0)) break;
                    if (it > SPIN_LIMIT) SPIN_FAIL(0x7000);
                    __nanosleep(100);
                }
                s0 = __uint_as_float((uint32_t)a); q0 = __uint_as_float((uint32_t)(a >> 32) & 0x7FFFFFFFu);
                s1 = __uint_as_float((uint32_t)b); q1 = __uint_as_float((uint32_t)(b >> 32) & 0x7FFFFFFFu);
                #pragma unroll
                for (int o = 1; o <= 2; o <<= 1) {
                    s0 += __shfl_xor_sync(0xffffffffu, s0, o); q0 += __shfl_xor_sync(0xffffffffu, q0, o);
                    s1 += __shfl_xor_sync(0xffffffffu, s1, o); q1 += __shfl_xor_sync(0xffffffffu, q1, o);
                }
            }
            const float m0 = s0 * (1.f / FH), m1 = s1 * (1.f / FH);
            const float rs0 = rsqrtf(fmaxf(q0 * (1.f / FH) - m0 * m0, 0.f) + 4e-5f), rs1 = rsqrtf(fmaxf(q1 * (1.f / FH) - m1 * m1, 0.f) + 4e-5f);
            const float c0 = -m0 * rs0, c1 = -m1 * rs1;
            uint8_t* dst = g_z2n + (size_t)(ct * 32 + rb) * 28672 + (2 * w) * 3584 + g * 16 + t * 4;
            #pragma unroll
            for (int j = 0; j < 14; j++) {
                *(uint32_t*)(dst + 2 * j * 128) = pack_bf16(fmaf(bf_lo(v[j].x), rs0, c0), fmaf(bf_hi(v[j].x), rs0, c0));
                *(uint32_t*)(dst + 3584 + 2 * j * 128) = pack_bf16(fmaf(bf_lo(v[j].y), rs1, c1), fmaf(bf_hi(v[j].y), rs1, c1));
                *(uint32_t*)(dst + (2 * j + 1) * 128) = pack_bf16(fmaf(bf_lo(v[j].z), rs0, c0), fmaf(bf_hi(v[j].z), rs0, c0));
                *(uint32_t*)(dst + 3584 + (2 * j + 1) * 128) = pack_bf16(fmaf(bf_lo(v[j].w), rs1, c1), fmaf(bf_hi(v[j].w), rs1, c1));
            }
            bar_sync(6, 128);
            if (tid == 0) flag_add(F_Z2 + rb * 4 + ct);
        }
        if (wg == 2) bar_sync(13, 256); else bar_sync(2, 384);
        const int p0 = wg == 2 ? 1 : 0;
        #define HEAD(ps) ((ps) == 0 ? wg : 3 * (ps) - 1 + wg)
        uint32_t qmax2 = 0;
        #pragma unroll 1
        for (int i = p0 + (tid >> 6); i < 3; i += 2) {
            uint8_t* qrow = sm + SM_Q + HEAD(i) * 3072 + (tid & 63) * 16;
            const uint4 a = *(const uint4*)qrow, b = *(const uint4*)(qrow + 1024);
            const uint2 c = *(const uint2*)(qrow + 2048);
            #define SQ(v) (bf_lo(v) * bf_lo(v) + bf_hi(v) * bf_hi(v))
            const float n = SQ(a.x) + SQ(a.y) + SQ(a.z) + SQ(a.w) + SQ(b.x) + SQ(b.y) + SQ(b.z) + SQ(b.w) + SQ(c.x) + SQ(c.y);
            qmax2 = max(qmax2, __float_as_uint(n) & 0x7FFFFFFFu);
            *(uint2*)(qrow + 2048 + 8) = make_uint2(0x3F803F80u, 0u);
        }
        asm volatile("fence.proxy.async.shared::cta;" ::: "memory");
        mbar_sleep(bar_kfull + 32, 0);
        bar_arrive(8, 512);
        uint32_t safe;
        {
            const float kmax2 = __uint_as_float(__reduce_max_sync(0xffffffffu, __float_as_uint(s_stat[lane])));
            const int ev = (int)(__reduce_max_sync(0xffffffffu, __float_as_uint(s_stat[32 + lane])) >> 23) - 126;
            const float bmax = fminf(100.f, fminf((float)(110 - max(ev, 1)), (float)(88 + ev)));
            const bool ok = bmax > 0.f && __uint_as_float(qmax2) * kmax2 <= bmax * bmax;
            asm volatile("{\n.reg .pred p, q;\nsetp.ne.u32 p, %1, 0;\nbarrier.red.and.pred.aligned q, %2, 128, p;\nselp.u32 %0, 1, 0, q;\n}"
                         : "=r"(safe) : "r"((uint32_t)ok), "r"(4 + wg) : "memory");
            safe = __shfl_sync(0xffffffffu, safe, 0);
            if (!safe) {
                #pragma unroll 1
                for (int i = p0 + (tid >> 6); i < 3; i += 2) *(uint2*)(sm + SM_Q + HEAD(i) * 3072 + (tid & 63) * 16 + 2048 + 8) = make_uint2(0u, 0u);
                asm volatile("fence.proxy.async.shared::cta;" ::: "memory");
                bar_sync(4 + wg, 128);
            }
        }
        const uint32_t kv16 = ((sb + SM_KV) & 0x3FFFFu) >> 4;
        constexpr uint32_t KLBO = 8u << 16, KHI = 24u, VLBO = (24u << 16) + 192u, VHI = 8u;
        const bool lead = lane == 0;
        const int r0 = 16 * w + g;
        static_assert(KST == 4, "ring phases below assume 4 stages");
        if (wg == 2) {
            bar_sync(14, 256);
            mbar_wait(bar_kfull + 24, 1);
        }
        const uint32_t q16 = ((sb + SM_Q) & 0x3FFFFu) >> 4;
        uint64_t qa = mkdesc(q16 + HEAD(p0) * 192 + (64u << 16), 8), qb = mkdesc(q16 + HEAD(p0) * 192 + 128 + ((uint32_t)(1536 - 128 - HEAD(p0) * 192) << 16), 8);
        #define NEXT_HEAD(ps) { const uint32_t d_ = (ps) == 0 ? 384 : 576; qa += d_; qb += (uint64_t)d_ - ((uint64_t)d_ << 16); }
        const uint64_t dk = mkdesc(kv16 + KLBO, KHI), dv = mkdesc(kv16 + VLBO, VHI);
        const uint32_t kep = bar_kempty + peer_off;
        uint32_t rc = lead ? (wg == 0 ? 2 : 1) : 0;
        float o[12];
        #pragma unroll
        for (int i = 0; i < 12; i++) o[i] = 0.f;
        float s[32]; uint32_t pa[16], pb[16];
        FENCE_F(o, 12);
        #define QK(off) wgmma_ss_n64<0, 0>(s, qa, dk + (off), 0); wgmma_ss_n64<0, 0>(s, qb, dk + (off) + 16, 1);
        #define PV(pp, off) wgmma_rs_n24<1>(o, pp[0], pp[1], pp[2], pp[3], dv + (off), 1); wgmma_rs_n24<1>(o, pp[4], pp[5], pp[6], pp[7], dv + (off) + 48, 1); \
                            wgmma_rs_n24<1>(o, pp[8], pp[9], pp[10], pp[11], dv + (off) + 96, 1); wgmma_rs_n24<1>(o, pp[12], pp[13], pp[14], pp[15], dv + (off) + 144, 1);
        #define STORE_O(h) { \
            const float l0 = __shfl_sync(0xffffffffu, o[8], (lane & ~3) | 2), l1 = __shfl_sync(0xffffffffu, o[10], (lane & ~3) | 2); \
            const float i0 = __fdividef(s_gate[r0], l0), i1 = __fdividef(s_gate[r0 + 8], l1);        \
            _Pragma("unroll") for (int b = 0; b < 3; b++) { \
                if (b < 2 || t < 2) { \
                    const int cq = 20 * (h) + 8 * b + 2 * t, col = cq < 32 ? ct * 32 + cq : (cq < 96 ? 96 + ct * 64 + cq : 288 + ct * 64 + cq); \
                    uint8_t* dst = g_op + (size_t)((rb * 80 + (col >> 3)) * 8 + 2 * w) * 128 + g * 16 + (col & 7) * 2; \
                    *(uint32_t*)dst = pack_bf16(o[4 * b] * i0, o[4 * b + 1] * i0); \
                    *(uint32_t*)(dst + 128) = pack_bf16(o[4 * b + 2] * i1, o[4 * b + 3] * i1); \
                } \
            } \
            _Pragma("unroll") for (int i = 0; i < 12; i++) o[i] = 0.f; \
            FENCE_F(o, 12); \
            __syncwarp(); \
 }
        if (safe) {
            wg_fence();
            QK(3 * 768 + 384)
            wg_commit();
            wg_wait<0>();
            FENCE_F(s, 32);
            release2n(bar_kempty + 24, kep + 24, rc);
            EXPBLK(pa, s);
            FENCE_R(pa, 16);
            #define HALF(off, pin, pout) \
                wg_fence(); \
                QK(off) \
                wg_commit(); \
                PV(pin, off) \
                wg_commit(); \
                wg_wait<1>(); \
                FENCE_F(s, 32); \
                EXPBLK(pout, s); \
                FENCE_R(pout, 16); \
                wg_wait<0>();
            #pragma unroll 1
            for (int J4 = 4 * p0; J4 < 12; J4++) {
                const uint32_t ph = J4 & 1;
                #pragma unroll
                for (int st = 0; st < 4; st++) {
                    mbar_wait(bar_kfull + 8 * st, ph);
                    if (st == 3 && J4 == 3 && wg == 0) bar_arrive(14, 256);
                    HALF(st * 768, pa, pb)
                    if (st == 3 && (J4 & 3) == 3 && J4 < 11) NEXT_HEAD(J4 >> 2)
                    HALF(st * 768 + 384, pb, pa)
                    if (st < 3) release2n(bar_kempty + 8 * st, kep + 8 * st, rc);
                }
                if ((J4 & 3) == 3) {
                    FENCE_F(o, 12);
                    STORE_O(HEAD(J4 >> 2))
                    rc = lead ? 1 : 0;
                }
                release2n(bar_kempty + 24, kep + 24, rc);
            }
        } else {
            float m0 = -INFINITY, m1 = -INFINITY;
            #pragma unroll 1
            for (int u = 32 * p0; u < 96; u++) {
                const int J = u >> 1;
                if ((u & 1) == 0) mbar_wait(bar_kfull + 8 * (J & 3), (J >> 2) & 1);
                if (u == 30 && wg == 0) bar_arrive(14, 256);
                wg_fence();
                QK(((u + 7) & 7) * 384)
                wg_commit();
                wg_wait<0>();
                FENCE_F(s, 32);
                float x0 = m0, x1 = m1;
                #pragma unroll
                for (int b = 0; b < 8; b++) {
                    const float f = ((PAT >> b) & 1) ? 0.5f : 1.f;
                    s[4 * b] *= f; s[4 * b + 1] *= f; s[4 * b + 2] *= f; s[4 * b + 3] *= f;
                    x0 = fmaxf(x0, fmaxf(s[4 * b], s[4 * b + 1])); x1 = fmaxf(x1, fmaxf(s[4 * b + 2], s[4 * b + 3]));
                }
                x0 = fmaxf(x0, __shfl_xor_sync(0xffffffffu, x0, 1)); x0 = fmaxf(x0, __shfl_xor_sync(0xffffffffu, x0, 2));
                x1 = fmaxf(x1, __shfl_xor_sync(0xffffffffu, x1, 1)); x1 = fmaxf(x1, __shfl_xor_sync(0xffffffffu, x1, 2));
                const float f0 = exp2f(m0 - x0), f1 = exp2f(m1 - x1);
                m0 = x0; m1 = x1;
                #pragma unroll
                for (int b = 0; b < 3; b++) { o[4 * b] *= f0; o[4 * b + 1] *= f0; o[4 * b + 2] *= f1; o[4 * b + 3] *= f1; }
                #pragma unroll
                for (int b = 0; b < 8; b++) {
                    pa[2 * b] = exp2_mufu(s[4 * b] - m0, s[4 * b + 1] - m0);
                    pa[2 * b + 1] = exp2_mufu(s[4 * b + 2] - m1, s[4 * b + 3] - m1);
                }
                FENCE_R(pa, 16); FENCE_F(o, 12);
                wg_fence();
                PV(pa, (u & 7) * 384)
                wg_commit();
                wg_wait<0>();
                FENCE_F(o, 12);
                if ((u & 1) == 0) release2n(bar_kempty + 8 * ((J + 3) & 3), kep + 8 * ((J + 3) & 3), rc);
                if ((u & 31) == 31) {
                    STORE_O(HEAD(u >> 5))
                    m0 = -INFINITY; m1 = -INFINITY;
                    NEXT_HEAD(u >> 5)
                    rc = lead ? 1 : 0;
                }
            }
        }
        bar_sync(4 + wg, 128);
        if (tid == 0) flag_add(F_O + rb * 3 + 2);
    }
}

typedef CUresult (*EncodeFn)(CUtensorMap*, CUtensorMapDataType, cuuint32_t, void*, const cuuint64_t*, const cuuint64_t*, const cuuint32_t*,
                             const cuuint32_t*, CUtensorMapInterleave, CUtensorMapSwizzle, CUtensorMapL2promotion, CUtensorMapFloatOOBfill);

void make_map(EncodeFn fn, CUtensorMap* m, const void* ptr, uint64_t cols, uint64_t rows, uint32_t bc, uint32_t br, CUtensorMapSwizzle sw) {
    cuuint64_t dims[2] = {cols, rows}, strides[1] = {cols * 2};
    cuuint32_t box[2] = {bc, br}, es[2] = {1, 1};
    fn(m, CU_TENSOR_MAP_DATA_TYPE_BFLOAT16, 2, const_cast<void*>(ptr), dims, strides, box, es, CU_TENSOR_MAP_INTERLEAVE_NONE, sw,
       CU_TENSOR_MAP_L2_PROMOTION_L2_128B, CU_TENSOR_MAP_FLOAT_OOB_FILL_NONE);
}

void make_map3(EncodeFn fn, CUtensorMap* m, const void* ptr, uint64_t cols, uint64_t rows, uint32_t natoms) {
    cuuint64_t dims[3] = {32, rows, cols / 32}, strides[2] = {cols * 2, 64};
    cuuint32_t box[3] = {32, 32, natoms}, es[3] = {1, 1, 1};
    fn(m, CU_TENSOR_MAP_DATA_TYPE_BFLOAT16, 3, const_cast<void*>(ptr), dims, strides, box, es, CU_TENSOR_MAP_INTERLEAVE_NONE, CU_TENSOR_MAP_SWIZZLE_64B,
       CU_TENSOR_MAP_L2_PROMOTION_L2_128B, CU_TENSOR_MAP_FLOAT_OOB_FILL_NONE);
}

}

extern "C" void kernel_launch(void* const* d_in, const int* in_sizes, int n_in, void* d_out, int out_size) {
    static EncodeFn fn = nullptr;
    if (!fn) {
        cudaDriverEntryPointQueryResult qr;
        void* f = nullptr;
        cudaGetDriverEntryPoint("cuTensorMapEncodeTiled", &f, cudaEnableDefault, &qr);
        fn = (EncodeFn)f;
        cudaFuncSetAttribute(mega_kernel, cudaFuncAttributeMaxDynamicSharedMemorySize, SM_TOTAL);
    }
    Params p;
    const __nv_bfloat16* x = (const __nv_bfloat16*)d_in[0];
    make_map(fn, &p.mx, x, DM, S_LEN, 64, 64, CU_TENSOR_MAP_SWIZZLE_128B);
    make_map(fn, &p.mwsp, d_in[7], S_LEN, S_LEN, 64, 64, CU_TENSOR_MAP_SWIZZLE_128B);
    make_map3(fn, &p.mwq, d_in[1], DM, DM, 5);
    make_map3(fn, &p.mwin, d_in[6], 2 * FH, DM, 7);
    p.x = x;
    p.wq = (const __nv_bfloat16*)d_in[1];
    p.win = (const __nv_bfloat16*)d_in[6];
    p.wk = (const __nv_bfloat16*)d_in[2];
    p.wv = (const __nv_bfloat16*)d_in[3];
    p.bsp = (const __nv_bfloat16*)d_in[8];
    p.gw = (const __nv_bfloat16*)d_in[10];
    p.wsp = (const __nv_bfloat16*)d_in[7];
    p.wo = (const __nv_bfloat16*)d_in[4];
    p.wout = (const __nv_bfloat16*)d_in[9];
    p.out = (__nv_bfloat16*)d_out;
    mega_kernel<<<NCTA, 640, SM_TOTAL>>>(p);
}
```

```cpp
#include <cuda_runtime.h>
#include <cuda_bf16.h>
#include <cuda.h>
#include <stdint.h>

namespace {

constexpr int S_LEN = 2048, DM = 640, FH = 864;
constexpr int NCTA = 128;
#define PAT8 0xB5u
constexpr uint32_t PAT = PAT8 * 0x101u;
#define GB2 -1
#define GB3 -1
#define GB4 2
#define GB5 -1
constexpr int GST = 4;
constexpr int GST_BYTES = 36864;
constexpr int KST = 4;
constexpr int KST_BYTES = 12288;
constexpr int QS_PITCH = 168;
constexpr int SM_G = 0;
constexpr int SM_KV = SM_G + GST * GST_BYTES;
constexpr int SM_Q = SM_KV + KST * KST_BYTES;
constexpr int SM_MISC = SM_Q + 8 * 3072 + 1024;
constexpr int SM_W = SM_G + 2 * GST_BYTES + 16384;
constexpr int SM_TOTAL = SM_MISC + 2048 + 1024;

constexpr int F_KV = 0, F_DONE = 1, F_WR = 2, F_Z2 = 3, F_H = F_Z2 + 128, F_O = F_H + 32, F_NUM = F_O + 96;

__device__ __align__(1024) uint8_t g_kv[16 * KST_BYTES];
__device__ __align__(1024) uint8_t g_z2n[4 * 32 * 28672];
__device__ __align__(1024) uint8_t g_hp[32 * 108 * 1024];
__device__ __align__(1024) uint8_t g_op[32 * 80 * 1024];
__device__ __align__(1024) uint8_t g_wot[4 * 80 * 2560];
__device__ __align__(1024) uint8_t g_woutt[4 * 108 * 2560];
__device__ __align__(1024) uint4 g_z1[2 * NCTA * 14 * 128];
__device__ unsigned long long g_part[32 * 4 * 64];
__device__ __align__(128) float g_kvmax[64];
__device__ __align__(128) float g_gate[S_LEN];
__device__ unsigned g_flags[F_NUM * 8];
__device__ uint32_t g_const[1] = {0x3F013F01u};

struct Params {
    CUtensorMap mx, mwsp, mwq, mwin;
    const __nv_bfloat16 *wk, *wv, *bsp, *gw, *wo, *wout, *wq, *win;
    __nv_bfloat16* out;
};

template<int TB> __device__ __forceinline__ void wgmma_rs_n24(float (&d)[12], uint32_t a0, uint32_t a1, uint32_t a2, uint32_t a3, uint64_t db, int scale_d) {
  asm volatile("{\n.reg .pred p;\nsetp.ne.b32 p, %17, 0;\nwgmma.mma_async.sync.aligned.m64n24k16.f32.bf16.bf16 {%0,%1,%2,%3,%4,%5,%6,%7,%8,%9,%10,%11}, {%12,%13,%14,%15}, %16, p, 1, 1, %18;\n}"
    : "+f"(d[0]), "+f"(d[1]), "+f"(d[2]), "+f"(d[3]), "+f"(d[4]), "+f"(d[5]), "+f"(d[6]), "+f"(d[7]), "+f"(d[8]), "+f"(d[9]), "+f"(d[10]), "+f"(d[11])
    : "r"(a0), "r"(a1), "r"(a2), "r"(a3), "l"(db), "r"(scale_d), "n"(TB));
}
template<int TA, int TB> __device__ __forceinline__ void wgmma_ss_n48(float (&d)[24], uint64_t da, uint64_t db, int scale_d) {
  asm volatile("{\n.reg .pred p;\nsetp.ne.b32 p, %26, 0;\nwgmma.mma_async.sync.aligned.m64n48k16.f32.bf16.bf16 {%0,%1,%2,%3,%4,%5,%6,%7,%8,%9,%10,%11,%12,%13,%14,%15,%16,%17,%18,%19,%20,%21,%22,%23}, %24, %25, p, 1, 1, %27, %28;\n}"
    : "+f"(d[0]), "+f"(d[1]), "+f"(d[2]), "+f"(d[3]), "+f"(d[4]), "+f"(d[5]), "+f"(d[6]), "+f"(d[7]), "+f"(d[8]), "+f"(d[9]), "+f"(d[10]), "+f"(d[11]), "+f"(d[12]), "+f"(d[13]), "+f"(d[14]), "+f"(d[15]), "+f"(d[16]), "+f"(d[17]), "+f"(d[18]), "+f"(d[19]), "+f"(d[20]), "+f"(d[21]), "+f"(d[22]), "+f"(d[23])
    : "l"(da), "l"(db), "r"(scale_d), "n"(TA), "n"(TB));
}
template<int TA, int TB> __device__ __forceinline__ void wgmma_ss_n64(float (&d)[32], uint64_t da, uint64_t db, int scale_d) {
  asm volatile("{\n.reg .pred p;\nsetp.ne.b32 p, %34, 0;\nwgmma.mma_async.sync.aligned.m64n64k16.f32.bf16.bf16 {%0,%1,%2,%3,%4,%5,%6,%7,%8,%9,%10,%11,%12,%13,%14,%15,%16,%17,%18,%19,%20,%21,%22,%23,%24,%25,%26,%27,%28,%29,%30,%31}, %32, %33, p, 1, 1, %35, %36;\n}"
    : "+f"(d[0]), "+f"(d[1]), "+f"(d[2]), "+f"(d[3]), "+f"(d[4]), "+f"(d[5]), "+f"(d[6]), "+f"(d[7]), "+f"(d[8]), "+f"(d[9]), "+f"(d[10]), "+f"(d[11]), "+f"(d[12]), "+f"(d[13]), "+f"(d[14]), "+f"(d[15]), "+f"(d[16]), "+f"(d[17]), "+f"(d[18]), "+f"(d[19]), "+f"(d[20]), "+f"(d[21]), "+f"(d[22]), "+f"(d[23]), "+f"(d[24]), "+f"(d[25]), "+f"(d[26]), "+f"(d[27]), "+f"(d[28]), "+f"(d[29]), "+f"(d[30]), "+f"(d[31])
    : "l"(da), "l"(db), "r"(scale_d), "n"(TA), "n"(TB));
}
template<int TA, int TB> __device__ __forceinline__ void wgmma_ss_n96(float (&d)[48], uint64_t da, uint64_t db, int scale_d) {
  asm volatile("{\n.reg .pred p;\nsetp.ne.b32 p, %50, 0;\nwgmma.mma_async.sync.aligned.m64n96k16.f32.bf16.bf16 {%0,%1,%2,%3,%4,%5,%6,%7,%8,%9,%10,%11,%12,%13,%14,%15,%16,%17,%18,%19,%20,%21,%22,%23,%24,%25,%26,%27,%28,%29,%30,%31,%32,%33,%34,%35,%36,%37,%38,%39,%40,%41,%42,%43,%44,%45,%46,%47}, %48, %49, p, 1, 1, %51, %52;\n}"
    : "+f"(d[0]), "+f"(d[1]), "+f"(d[2]), "+f"(d[3]), "+f"(d[4]), "+f"(d[5]), "+f"(d[6]), "+f"(d[7]), "+f"(d[8]), "+f"(d[9]), "+f"(d[10]), "+f"(d[11]), "+f"(d[12]), "+f"(d[13]), "+f"(d[14]), "+f"(d[15]), "+f"(d[16]), "+f"(d[17]), "+f"(d[18]), "+f"(d[19]), "+f"(d[20]), "+f"(d[21]), "+f"(d[22]), "+f"(d[23]), "+f"(d[24]), "+f"(d[25]), "+f"(d[26]), "+f"(d[27]), "+f"(d[28]), "+f"(d[29]), "+f"(d[30]), "+f"(d[31]), "+f"(d[32]), "+f"(d[33]), "+f"(d[34]), "+f"(d[35]), "+f"(d[36]), "+f"(d[37]), "+f"(d[38]), "+f"(d[39]), "+f"(d[40]), "+f"(d[41]), "+f"(d[42]), "+f"(d[43]), "+f"(d[44]), "+f"(d[45]), "+f"(d[46]), "+f"(d[47])
    : "l"(da), "l"(db), "r"(scale_d), "n"(TA), "n"(TB));
}
template<int TA, int TB> __device__ __forceinline__ void wgmma_ss_n128(float (&d)[64], uint64_t da, uint64_t db, int scale_d) {
  asm volatile("{\n.reg .pred p;\nsetp.ne.b32 p, %66, 0;\nwgmma.mma_async.sync.aligned.m64n128k16.f32.bf16.bf16 {%0,%1,%2,%3,%4,%5,%6,%7,%8,%9,%10,%11,%12,%13,%14,%15,%16,%17,%18,%19,%20,%21,%22,%23,%24,%25,%26,%27,%28,%29,%30,%31,%32,%33,%34,%35,%36,%37,%38,%39,%40,%41,%42,%43,%44,%45,%46,%47,%48,%49,%50,%51,%52,%53,%54,%55,%56,%57,%58,%59,%60,%61,%62,%63}, %64, %65, p, 1, 1, %67, %68;\n}"
    : "+f"(d[0]), "+f"(d[1]), "+f"(d[2]), "+f"(d[3]), "+f"(d[4]), "+f"(d[5]), "+f"(d[6]), "+f"(d[7]), "+f"(d[8]), "+f"(d[9]), "+f"(d[10]), "+f"(d[11]), "+f"(d[12]), "+f"(d[13]), "+f"(d[14]), "+f"(d[15]), "+f"(d[16]), "+f"(d[17]), "+f"(d[18]), "+f"(d[19]), "+f"(d[20]), "+f"(d[21]), "+f"(d[22]), "+f"(d[23]), "+f"(d[24]), "+f"(d[25]), "+f"(d[26]), "+f"(d[27]), "+f"(d[28]), "+f"(d[29]), "+f"(d[30]), "+f"(d[31]), "+f"(d[32]), "+f"(d[33]), "+f"(d[34]), "+f"(d[35]), "+f"(d[36]), "+f"(d[37]), "+f"(d[38]), "+f"(d[39]), "+f"(d[40]), "+f"(d[41]), "+f"(d[42]), "+f"(d[43]), "+f"(d[44]), "+f"(d[45]), "+f"(d[46]), "+f"(d[47]), "+f"(d[48]), "+f"(d[49]), "+f"(d[50]), "+f"(d[51]), "+f"(d[52]), "+f"(d[53]), "+f"(d[54]), "+f"(d[55]), "+f"(d[56]), "+f"(d[57]), "+f"(d[58]), "+f"(d[59]), "+f"(d[60]), "+f"(d[61]), "+f"(d[62]), "+f"(d[63])
    : "l"(da), "l"(db), "r"(scale_d), "n"(TA), "n"(TB));
}

__device__ __forceinline__ uint64_t mkdesc(uint32_t lo, uint32_t hi) { uint64_t d; asm("mov.b64 %0, {%1, %2};" : "=l"(d) : "r"(lo), "r"(hi)); return d; }
__device__ __forceinline__ void mbar_init(uint32_t a, int c) { asm volatile("mbarrier.init.shared::cta.b64 [%0], %1;" :: "r"(a), "r"(c)); }
__device__ __forceinline__ void mbar_expect(uint32_t a, uint32_t b) { asm volatile("mbarrier.arrive.expect_tx.shared::cta.b64 _, [%0], %1;" :: "r"(a), "r"(b) : "memory"); }
__device__ __forceinline__ void mbar_arrive(uint32_t a) { asm volatile("mbarrier.arrive.shared::cta.b64 _, [%0];" :: "r"(a) : "memory"); }
#define SPIN_LIMIT (1 << 20)
#define SPIN_FAIL(code) __trap()
__device__ __forceinline__ void mbar_wait(uint32_t a, uint32_t ph) {
    asm volatile("{\n.reg .pred p, q;\n.reg .u32 c;\nmov.u32 c, 0;\n"
                 "W0:\nmbarrier.try_wait.parity.shared::cta.b64 p, [%0], %1;\n@p bra W1;\n"
                 "add.u32 c, c, 1;\nsetp.lt.u32 q, c, %2;\n@q bra W0;\ntrap;\n"
                 "W1:\n}" :: "r"(a), "r"(ph), "n"(4 * SPIN_LIMIT) : "memory");
}
__device__ __forceinline__ void mbar_sleep(uint32_t a, uint32_t ph) {
    asm volatile("{\n.reg .pred p, q;\n.reg .u32 c;\nmov.u32 c, 0;\n"
                 "W0:\nmbarrier.try_wait.parity.shared::cta.b64 p, [%0], %1, 4000;\n@p bra W1;\n"
                 "add.u32 c, c, 1;\nsetp.lt.u32 q, c, %2;\n@q bra W0;\ntrap;\n"
                 "W1:\n}" :: "r"(a), "r"(ph), "n"(SPIN_LIMIT) : "memory");
}
__device__ __forceinline__ void wg_fence() { asm volatile("wgmma.fence.sync.aligned;" ::: "memory"); }
__device__ __forceinline__ void wg_commit() { asm volatile("wgmma.commit_group.sync.aligned;" ::: "memory"); }
template<int N> __device__ __forceinline__ void wg_wait() { asm volatile("wgmma.wait_group.sync.aligned %0;" :: "n"(N) : "memory"); }
__device__ __forceinline__ void bar_sync(int id, int n) { asm volatile("bar.sync %0, %1;" :: "r"(id), "r"(n) : "memory"); }
__device__ __forceinline__ void bar_arrive(int id, int n) { asm volatile("bar.arrive %0, %1;" :: "r"(id), "r"(n) : "memory"); }
__device__ __forceinline__ void fence_async() { asm volatile("fence.proxy.async.global;" ::: "memory"); }
__device__ __forceinline__ void flag_wait(int f, unsigned target) {
    const unsigned* p = &g_flags[f * 8];
    unsigned v;
    #pragma unroll 1
    for (int it = 0; it < SPIN_LIMIT; it++) {
        asm volatile("ld.acquire.gpu.global.u32 %0, [%1];" : "=r"(v) : "l"(p) : "memory");
        if (v >= target) return;
        __nanosleep(20);
    }
    SPIN_FAIL(f);
}
__device__ __forceinline__ void flag_add(int f) { asm volatile("red.release.gpu.global.add.u32 [%0], 1;" :: "l"(&g_flags[f * 8]) : "memory"); }
__device__ __forceinline__ void tma2d(uint32_t dst, const CUtensorMap* m, int c0, int c1, uint32_t bar) {
    asm volatile("cp.async.bulk.tensor.2d.shared::cluster.global.mbarrier::complete_tx::bytes [%0], [%1, {%3, %4}], [%2];"
        :: "r"(dst), "l"(m), "r"(bar), "r"(c0), "r"(c1) : "memory");
}
__device__ __forceinline__ void bulk_ld(uint32_t dst, const void* src, uint32_t bytes, uint32_t bar) {
    asm volatile("cp.async.bulk.shared::cluster.global.mbarrier::complete_tx::bytes [%0], [%1], %2, [%3];"
        :: "r"(dst), "l"(src), "r"(bytes), "r"(bar) : "memory");
}
__device__ __forceinline__ void tma3d_mc(uint32_t dst, const CUtensorMap* m, int c1, int c2, uint32_t bar) {
    asm volatile("cp.async.bulk.tensor.3d.shared::cluster.global.mbarrier::complete_tx::bytes.multicast::cluster [%0], [%1, {0, %3, %4}], [%2], %5;"
        :: "r"(dst), "l"(m), "r"(bar), "r"(c1), "r"(c2), "h"((uint16_t)3) : "memory");
}
__device__ __forceinline__ void bulk_ld_mc(uint32_t dst, const void* src, uint32_t bytes, uint32_t bar) {
    asm volatile("cp.async.bulk.shared::cluster.global.mbarrier::complete_tx::bytes.multicast::cluster [%0], [%1], %2, [%3], %4;"
        :: "r"(dst), "l"(src), "r"(bytes), "r"(bar), "h"((uint16_t)3) : "memory");
}
__device__ __forceinline__ void release2(uint32_t a, uint32_t peer_off) {
    asm volatile("mbarrier.arrive.shared::cta.b64 _, [%0];\nmbarrier.arrive.shared::cluster.b64 _, [%1];" :: "r"(a), "r"(a + peer_off) : "memory");
}
__device__ __forceinline__ void release2n(uint32_t a, uint32_t pa, uint32_t cnt) {
    asm volatile("{\n.reg .pred p;\nsetp.ne.u32 p, %2, 0;\n@p mbarrier.arrive.shared::cta.b64 _, [%0], %2;\n@p mbarrier.arrive.shared::cluster.b64 _, [%1], %2;\n}"
                 :: "r"(a), "r"(pa), "r"(cnt) : "memory");
}
__device__ __forceinline__ bool elect_one() {
    uint32_t p;
    asm volatile("{\n.reg .pred q;\nelect.sync _|q, 0xffffffff;\nselp.u32 %0, 1, 0, q;\n}" : "=r"(p));
    return p != 0;
}
__device__ __forceinline__ void l2_prefetch(const void* src, uint32_t bytes) {
    asm volatile("cp.async.bulk.prefetch.L2.global [%0], %1;" :: "l"(src), "r"(bytes) : "memory");
}
__device__ __forceinline__ uint32_t pack_bf16(float lo, float hi) { uint32_t r; asm("cvt.rn.bf16x2.f32 %0, %1, %2;" : "=r"(r) : "f"(hi), "f"(lo)); return r; }
__device__ __forceinline__ float bf_lo(uint32_t v) { return __uint_as_float(v << 16); }
__device__ __forceinline__ float bf_hi(uint32_t v) { return __uint_as_float(v & 0xFFFF0000u); }
__device__ __forceinline__ float gelu2_tanh(float x) {
    float u = x * fmaf(x * x, 0.0356774081363001f, 0.7978845608028654f), t;
    asm("tanh.approx.f32 %0, %1;" : "=f"(t) : "f"(u));
    return fmaf(x, t, x);
}
#define FENCE_F(a, n) _Pragma("unroll") for (int i_ = 0; i_ < n; i_++) asm volatile("" : "+f"(a[i_]) :: "memory");
#define FENCE_R(a, n) _Pragma("unroll") for (int i_ = 0; i_ < n; i_++) asm volatile("" : "+r"(a[i_]) :: "memory");

__device__ __forceinline__ uint32_t exp2_mufu(float a, float b) {
    float x, y;
    asm("ex2.approx.ftz.f32 %0, %1;" : "=f"(x) : "f"(a));
    asm("ex2.approx.ftz.f32 %0, %1;" : "=f"(y) : "f"(b));
    return pack_bf16(x, y);
}
__device__ __forceinline__ uint32_t exp2_alu(float a, float b, uint32_t half2c) {
    uint32_t L = __byte_perm(__float_as_uint(a), __float_as_uint(b), 0x6521), G, E, r;
    asm("lop3.b32 %0, %1, 0x007F007F, %2, 0xE2;" : "=r"(G) : "r"(L), "r"(half2c));
    asm("lop3.b32 %0, %1, 0x007F007F, %2, 0xB8;" : "=r"(E) : "r"(L), "r"(half2c));
    asm("fma.rn.bf16x2 %0, %1, %2, %3;" : "=r"(r) : "r"(G), "r"(L), "r"(E));
    return r;
}
#define EXPBLK(p, s) _Pragma("unroll") for (int b = 0; b < 8; b++) { \
    if ((PAT >> b) & 1) { p[2*b] = exp2_alu(s[4*b], s[4*b+1], half2c); p[2*b+1] = exp2_alu(s[4*b+2], s[4*b+3], half2c); } \
    else { p[2*b] = exp2_mufu(s[4*b], s[4*b+1]); p[2*b+1] = exp2_mufu(s[4*b+2], s[4*b+3]); } }

struct Ring { uint32_t st, ph; };
template<int NST> __device__ __forceinline__ void ring_next(Ring& r) { if (++r.st == NST) { r.st = 0; r.ph ^= 1; } }

struct OpDesc { uint32_t lo, hi, step, step2, nsplit; };

template<int N, int PART> __device__ __forceinline__ void wgmma_ss(float (&d)[N / 2], uint64_t da, uint64_t db, int sc) {
    if constexpr (N == 160) {
        if constexpr (PART == 0) wgmma_ss_n96<0, 1>(*(float(*)[48])&d[0], da, db, sc);
        else wgmma_ss_n64<0, 1>(*(float(*)[32])&d[48], da, db, sc);
    } else if constexpr (N == 192) {
        if constexpr (PART == 0) wgmma_ss_n128<0, 1>(*(float(*)[64])&d[0], da, db, sc);
        else wgmma_ss_n64<0, 1>(*(float(*)[32])&d[64], da, db, sc);
    } else {
        if constexpr (PART == 0) wgmma_ss_n128<0, 1>(*(float(*)[64])&d[0], da, db, sc);
        else wgmma_ss_n96<0, 1>(*(float(*)[48])&d[64], da, db, sc);
    }
}

struct GemmCtx { Ring r; uint32_t sb16, bar_full, bar_empty, peer_off; bool lead; };

template<int N, int NS, int GB>
__device__ __forceinline__ void gemm_loop(float (&acc)[N / 2], int nkb, int first, OpDesc a, OpDesc b, GemmCtx& c) {
    uint32_t prev = 0;
    #pragma unroll 1
    for (int kb = 0; kb < nkb; kb++) {
        mbar_sleep(c.bar_full + 8 * c.r.st, c.r.ph);
        const uint32_t base = c.sb16 + c.r.st * (GST_BYTES / 16);
        const uint64_t da0 = mkdesc(base + a.lo, a.hi), db0 = mkdesc(base + b.lo, b.hi);
        wg_fence();
        #pragma unroll
        for (int k = 0; k < NS; k++) {
            const uint64_t da = da0 + k * a.step, db = db0 + ((k & 1) * b.step + (k >> 1) * b.step2);
            const int sc = (k > 0) | (kb > 0) | !first;
            wgmma_ss<N, 0>(acc, da, db, sc);
            if constexpr (GB > 0) { wg_commit(); wg_wait<GB - 1>(); }
            wgmma_ss<N, 1>(acc, da, db + b.nsplit, sc);
            if constexpr (GB < 0) {
                if ((k + 1) % (-GB) == 0 || k == NS - 1) {
                    wg_commit(); wg_wait<1>();
                    if (k < -GB && kb > 0 && c.lead) release2(c.bar_empty + 8 * prev, c.peer_off);
                }
            }
            if constexpr (GB > 0) {
                wg_commit(); wg_wait<GB - 1>();
                if (k == (GB - 1) / 2 && kb > 0 && c.lead) release2(c.bar_empty + 8 * prev, c.peer_off);
            }
        }
        if constexpr (GB == 0) {
            wg_commit();
            wg_wait<1>();
            if (kb > 0 && c.lead) release2(c.bar_empty + 8 * prev, c.peer_off);
        }
        prev = c.r.st;
        ring_next<GST>(c.r);
    }
    wg_wait<0>();
    if (c.lead) release2(c.bar_empty + 8 * prev, c.peer_off);
    FENCE_F(acc, N / 2);
}

template<int CNT, int SUBS>
__device__ __forceinline__ void retile_ld(uint4 (&v)[CNT], const __nv_bfloat16* src, int pitch, int ncg, int nkg, int cm0, int cnt, int id) {
    const int sub = id >> 3, row = id & 7;
    #pragma unroll
    for (int i = 0; i < CNT; i++) {
        const int l = sub + i * SUBS, cm = cm0 + l, kg = cm / ncg, cg = cm - kg * ncg;
        if (l < cnt && kg < nkg) v[i] = __ldg((const uint4*)(src + (size_t)(kg * 8 + row) * pitch + cg * 8));
    }
}
template<int NG, int CNT, int SUBS, bool PERM>
__device__ __forceinline__ void retile_st(const uint4 (&v)[CNT], int ncg, int nkg, uint8_t* dst, int cm0, int cnt, int id) {
    const int sub = id >> 3, row = id & 7;
    #pragma unroll
    for (int i = 0; i < CNT; i++) {
        const int l = sub + i * SUBS, cm = cm0 + l, kg = cm / ncg, cg = cm - kg * ncg, tile = cg / NG;
        int kd = kg;
        if (PERM) { const int q = kg / 20, rem = kg - q * 20; kd = rem < 4 ? q * 4 + rem : (rem < 12 ? 12 + q * 8 + rem : 36 + q * 8 + rem); }
        if (l < cnt && kg < nkg) *(uint4*)(dst + (size_t)((tile * nkg + kd) * NG + (cg - tile * NG)) * 128 + row * 16) = v[i];
    }
}

__global__ void __cluster_dims__(2, 1, 1) __launch_bounds__(640, 1) mega_kernel(const __grid_constant__ Params p) {
    extern __shared__ uint8_t smem_raw[];
    const uint32_t sb = ((uint32_t)__cvta_generic_to_shared(smem_raw) + 1023u) & ~1023u;
    uint8_t* sm = smem_raw + (sb - (uint32_t)__cvta_generic_to_shared(smem_raw));
    const uint32_t bar_gfull = sb + SM_MISC, bar_gempty = bar_gfull + 64, bar_kfull = bar_gfull + 128, bar_kempty = bar_gfull + 192;
    float* s_gate = (float*)(sm + SM_MISC + 256);
    float* s_stat = (float*)(sm + SM_MISC + 512);
    float* s_red = (float*)(sm + SM_MISC + 768);
    const int rb = blockIdx.x & 31, ct = blockIdx.x >> 5;
    const int rank = rb & 1;
    const int wg = __shfl_sync(0xffffffffu, threadIdx.x >> 7, 0);
    const int tid = threadIdx.x & 127, w = tid >> 5, lane = tid & 31, g = lane >> 2, t = lane & 3;
    uint32_t peer_off;
    asm("mapa.shared::cluster.u32 %0, %1, %2;" : "=r"(peer_off) : "r"(sb), "r"(rank ^ 1));
    peer_off -= sb;

    if (threadIdx.x >= 576 && threadIdx.x < 580) asm volatile("prefetch.tensormap [%0];" :: "l"(&p.mx + (threadIdx.x - 576)) : "memory");
    if (threadIdx.x == 544) {
        l2_prefetch(p.wq + (size_t)blockIdx.x * 3200, 6400);
        l2_prefetch(p.win + (size_t)blockIdx.x * 8640, 17280);
    }
    if (__shfl_sync(0xffffffffu, threadIdx.x >> 5, 0) == 16 && elect_one()) {
        for (int i = 0; i < GST; i++) { mbar_init(bar_gfull + 8 * i, 1); mbar_init(bar_gempty + 8 * i, 8); }
        for (int i = 0; i < KST; i++) { mbar_init(bar_kfull + 8 * i, 1); mbar_init(bar_kempty + 8 * i, 24); }
        mbar_init(bar_kfull + 32, 1); mbar_init(bar_kfull + 40, 1); mbar_init(bar_kfull + 48, 1);
        asm volatile("fence.mbarrier_init.release.cluster;" ::: "memory");
        asm volatile("fence.proxy.async.shared::cta;" ::: "memory");
        if (ct == 3) {
            mbar_arrive(bar_gfull + 24);
            mbar_expect(bar_kfull + 48, 2 * 25600 + 1280);
            bulk_ld(sb + SM_W, p.wk, 25600, bar_kfull + 48);
            bulk_ld(sb + SM_W + 25600, p.wv, 25600, bar_kfull + 48);
            bulk_ld(sb + SM_W + 51200, p.gw, 1280, bar_kfull + 48);
            #pragma unroll 1
            for (int kb = 0; kb < 10; kb++) {
                if ((kb & 3) == 0) mbar_expect(bar_gfull + (kb >> 2) * 8, kb < 8 ? 32768 : 16384);
                tma2d(sb + SM_G + (kb >> 2) * GST_BYTES + (kb & 3) * 8192, &p.mx, kb * 64, rb * 64, bar_gfull + (kb >> 2) * 8);
            }
        }
    }
    asm volatile("barrier.cluster.arrive.relaxed;\nbarrier.cluster.wait.acquire;" ::: "memory");

    if (wg == 4) {
        asm volatile("setmaxnreg.dec.sync.aligned.u32 24;");
        const int wu = __shfl_sync(0xffffffffu, w, 0);
        static_assert(GST == 4, "ring indices are derived from a running stage counter");
        #define STG_ADDR(n) (sb + SM_G + ((n) & 3) * GST_BYTES)
        #define STG_FULL(n) (bar_gfull + ((n) & 3) * 8)
        #define STG_WAIT(n) mbar_sleep(bar_gempty + ((n) & 3) * 8, (((n) >> 2) & 1) ^ 1)
        const uint32_t n0 = ct == 3 ? 4 : 0;
        if (wu == 0) {
            uint32_t n = n0;
            if (elect_one()) {
                #pragma unroll 1
                for (int kb = 0; kb < 10; kb++, n++) {
                    STG_WAIT(n);
                    mbar_expect(STG_FULL(n), 8192 + 20480);
                    tma3d_mc(STG_ADDR(n) + 8192 + rank * 10240, &p.mwq, kb * 64 + rank * 32, 5 * ct, STG_FULL(n));
                }
                #pragma unroll 1
                for (int i = 0; i < 20; i++, n++) {
                    STG_WAIT(n);
                    mbar_expect(STG_FULL(n), 8192 + 28672);
                    tma3d_mc(STG_ADDR(n) + 8192 + rank * 14336, &p.mwin, (i < 10 ? i : i - 10) * 64 + rank * 32, (i < 10 ? 27 : 0) + 7 * ct, STG_FULL(n));
                }
            }
            __syncwarp();
            #pragma unroll 1
            for (int it = 0; ; it++) {
                unsigned v;
                asm volatile("ld.acquire.gpu.global.u32 %0, [%1];" : "=r"(v) : "l"(&g_flags[(F_Z2 + lane * 4 + ct) * 8]) : "memory");
                if (__all_sync(0xffffffffu, v != 0)) break;
                if (it > SPIN_LIMIT) SPIN_FAIL(F_Z2);
                __nanosleep(20);
            }
            if (elect_one()) {
                n = n0 + 30;
                fence_async();
                const uint8_t* src = g_z2n + (size_t)ct * 32 * 28672 + rank * 14336;
                #pragma unroll 1
                for (int kb = 0; kb < 32; kb++, n++, src += 28672) {
                    STG_WAIT(n);
                    mbar_expect(STG_FULL(n), 8192 + 28672);
                    bulk_ld_mc(STG_ADDR(n) + 8192 + rank * 14336, src, 14336, STG_FULL(n));
                }
                flag_wait(F_WR, 96);
                fence_async();
                n++;
                #pragma unroll 1
                for (int i = 0; i < 2; i++, n++) {
                    STG_WAIT(n);
                    mbar_expect(STG_FULL(n), 28672);
                    bulk_ld_mc(STG_ADDR(n) + 8192 + rank * 10240, g_wot + (size_t)(ct * 80 + i * 8) * 2560 + rank * 10240, 10240, STG_FULL(n));
                }
                uint32_t k0 = 28 * ct + rank * 4;
                #pragma unroll 1
                for (int i = 0; i < 14; i++, n++) {
                    const uint32_t nk = i == 13 ? 2 : 4;
                    if (i == 13) k0 -= rank * 2;
                    if (k0 >= 108) k0 -= 108;
                    STG_WAIT(n);
                    mbar_expect(STG_FULL(n), nk * 2 * (2560 + 1024));
                    bulk_ld_mc(STG_ADDR(n) + 8192 + rank * nk * 2560, g_woutt + (size_t)(ct * 108 + k0) * 2560, nk * 2560, STG_FULL(n));
                    k0 += 8;
                }
                #pragma unroll 1
                for (int i = 2; i < 10; i++, n++) {
                    STG_WAIT(n);
                    mbar_expect(STG_FULL(n), 28672);
                    bulk_ld_mc(STG_ADDR(n) + 8192 + rank * 10240, g_wot + (size_t)(ct * 80 + i * 8) * 2560 + rank * 10240, 10240, STG_FULL(n));
                }
            }
        } else if (wu == 3) {
            if (elect_one()) {
                uint32_t n = n0;
                #pragma unroll 1
                for (int j = 0; j < 3; j++) {
                    #pragma unroll 1
                    for (int kb = 0; kb < 10; kb++, n++) {
                        STG_WAIT(n);
                        tma2d(STG_ADDR(n), &p.mx, kb * 64, rb * 64, STG_FULL(n));
                    }
                }
                #define STASH_STAGE(which) { STG_WAIT(n); fence_async(); mbar_expect(STG_FULL(n), 28672); \
                    bulk_ld(STG_ADDR(n), g_z1 + (size_t)((which) * NCTA + blockIdx.x) * 1792, 28672, STG_FULL(n)); n++; }
                #pragma unroll 1
                for (int kb = 0; kb < 32; kb++, n++) {
                    STG_WAIT(n);
                    tma2d(STG_ADDR(n), &p.mwsp, kb * 64, rb * 64, STG_FULL(n));
                }
                STASH_STAGE(0)
                const uint8_t* op = g_op + (size_t)rb * 80 * 1024;
                const uint8_t* hp = g_hp + (size_t)rb * 108 * 1024;
                flag_wait(F_O + rb * 3, 4);
                fence_async();
                #pragma unroll 1
                for (int i = 0; i < 2; i++, n++) { STG_WAIT(n); bulk_ld(STG_ADDR(n), op + i * 8192, 8192, STG_FULL(n)); }
                mbar_sleep(bar_kfull + 40, 0);
                fence_async();
                uint32_t k0 = 28 * ct;
                #pragma unroll 1
                for (int i = 0; i < 14; i++, n++) {
                    if (i == 3) { flag_wait(F_H + rb, 4); fence_async(); }
                    STG_WAIT(n);
                    const uint32_t nb = (i == 13 || k0 == 104) ? 4096 : 8192;
                    bulk_ld(STG_ADDR(n), hp + k0 * 1024, nb, STG_FULL(n));
                    if (k0 == 104 && i != 13) bulk_ld(STG_ADDR(n) + 4096, hp, 4096, STG_FULL(n));
                    k0 += 8; if (k0 >= 108) k0 -= 108;
                }
                #pragma unroll 1
                for (int i = 2; i < 10; i++, n++) {
                    if (i == 2 || i == 6) { flag_wait(F_O + rb * 3 + (i == 2 ? 1 : 2), i == 2 ? 4 : 12); fence_async(); }
                    STG_WAIT(n);
                    bulk_ld(STG_ADDR(n), op + i * 8192, 8192, STG_FULL(n));
                }
            }
            __syncwarp();
            unsigned d = 0;
            if (lane == 0) d = atomicAdd(&g_flags[F_DONE * 8], 1u);
            if (__shfl_sync(0xffffffffu, d, 0) == NCTA - 1) {
                #pragma unroll
                for (int i = 0; i < (F_NUM + 31) / 32; i++) if (i * 32 + lane < F_NUM) g_flags[(i * 32 + lane) * 8] = 0;
            }
        } else if (wu == 1) {
            if (elect_one()) {
                flag_wait(F_KV, 32);
                asm volatile("fence.proxy.async.global;" ::: "memory");
                mbar_expect(bar_kfull + 32, 6144 + 512);
                bulk_ld(sb + SM_KV + 3 * KST_BYTES + 6144, g_kv + 31 * 6144, 6144, bar_kfull + 32);
                bulk_ld(sb + SM_MISC + 512, g_kvmax, 256, bar_kfull + 32);
                bulk_ld(sb + SM_MISC + 256, g_gate + rb * 64, 256, bar_kfull + 32);
                #pragma unroll 1
                for (int i = 0; i < 48; i++) {
                    const uint32_t st = i & 3;
                    if (i >= 3) mbar_sleep(bar_kempty + 8 * st, (((i + 1) >> 2) & 1) ^ 1);
                    mbar_expect(bar_kfull + 8 * st, KST_BYTES);
                    bulk_ld_mc(sb + SM_KV + st * KST_BYTES + rank * 6144, g_kv + (i & 15) * KST_BYTES + rank * 6144, 6144, bar_kfull + 8 * st);
                    if (i == 19 || i == 35) flag_add(F_O + rb * 3 + (i == 35));
                }
            }
        } else {
            if (ct == 3) {
                bar_sync(10, 160);
                if (lane < 2) {
                    const float* r = s_red + 8 + 4 * lane;
                    g_kvmax[lane * 32 + rb] = __uint_as_float(max(max(__float_as_uint(r[0]), __float_as_uint(r[1])), max(__float_as_uint(r[2]), __float_as_uint(r[3]))));
                }
                __syncwarp();
                if (elect_one()) flag_add(F_KV);
                __syncwarp();
            }
            bar_sync(10, 160);
            if (elect_one()) { flag_add(F_H + rb); mbar_arrive(bar_kfull + 40); }
        }
    } else if (wg == 3) {
        asm volatile("setmaxnreg.inc.sync.aligned.u32 144;");
        GemmCtx c{{0, 0}, ((sb + SM_G) & 0x3FFFFu) >> 4, bar_gfull, bar_gempty, peer_off, lane == 0};
        const OpDesc a_sw{0u, 64u | (1u << 30), 2u, 0u, 0u};
        const OpDesc a_t{64u << 16, 8u, 128u, 0u, 0u};
        const OpDesc b_q{512u | (128u << 16), 32u | (2u << 30), 64u, 640u, 384u};
        const OpDesc b_w{512u | (128u << 16), 32u | (2u << 30), 64u, 896u, 512u};
        const OpDesc b_z{512u | (224u << 16), 8u, 448u, 896u, 128u};
        const OpDesc b_o{512u | (160u << 16), 8u, 320u, 640u, 96u};
        const int r0 = 16 * w + g;
        if (ct == 3) {
            float ex[24];
            const uint32_t exlo = (((sb + SM_KV) & 0x3FFFFu) >> 4) | (48u << 16);
            bar_sync(1, 512);
            #pragma unroll 1
            for (int kb = 0; kb < 10; kb++) {
                if ((kb & 3) == 0) mbar_wait(bar_gfull + 8 * (kb >> 2), 0);
                const uint32_t base = c.sb16 + (kb >> 2) * (GST_BYTES / 16) + (kb & 3) * 512;
                wg_fence();
                #pragma unroll
                for (int k = 0; k < 4; k++) wgmma_ss_n48<0, 1>(ex, mkdesc(base + 2 * k, a_sw.hi), mkdesc(exlo + (kb * 4 + k) * 96, 8), (k > 0) | (kb > 0));
                wg_commit();
            }
            wg_wait<0>();
            FENCE_F(ex, 24);
            if (lane < 4) release2(bar_gempty + 8 * lane, peer_off);
            c.r.ph = 1;
            uint8_t* dk = g_kv + ((rb + 31) & 31) * 6144 + 2 * w * 384 + g * 16 + t * 4;
            uint8_t* dv = g_kv + rb * 6144 + 3072 + 2 * w * 384 + g * 16 + t * 4;
            uint32_t mk = 0, mv = 0;
            #pragma unroll
            for (int hi = 0; hi < 2; hi++) {
                const bool alu = (PAT >> (2 * w + hi)) & 1;
                float n2 = 0.f;
                #pragma unroll
                for (int j = 0; j < 3; j++) {
                    uint32_t v = pack_bf16(ex[4 * j + 2 * hi], ex[4 * j + 2 * hi + 1]);
                    const float a = bf_lo(v), b = bf_hi(v);
                    n2 = fmaf(a, a, fmaf(b, b, n2));
                    if (alu) v = pack_bf16(2.f * a, 2.f * b);
                    if (j == 2 && t == 2) v = alu ? 0x3C004446u : 0x3CF14159u;
                    *(uint32_t*)(dk + hi * 384 + j * 128) = v;
                    v = pack_bf16(ex[12 + 4 * j + 2 * hi], ex[12 + 4 * j + 2 * hi + 1]);
                    if (j < 2 || t < 2) mv = max(mv, max((v << 16) & 0x7FFF0000u, v & 0x7FFF0000u));
                    if (j == 2 && t == 3) {
                        g_gate[rb * 64 + r0 + 8 * hi] = 1.f / (1.f + __expf(-ex[20 + 2 * hi]));
                        v = 0u;
                    }
                    if (j == 2 && t == 2) v = 0x00003F80u;
                    *(uint32_t*)(dv + hi * 384 + j * 128) = v;
                }
                n2 += __shfl_xor_sync(0xffffffffu, n2, 1); n2 += __shfl_xor_sync(0xffffffffu, n2, 2);
                mk = max(mk, __float_as_uint(n2) & 0x7FFFFFFFu);
            }
            mk = __reduce_max_sync(0xffffffffu, mk); mv = __reduce_max_sync(0xffffffffu, mv);
            if (lane == 0) { s_red[8 + w] = __uint_as_float(mk); s_red[12 + w] = __uint_as_float(mv); }
            bar_arrive(10, 160);
        }
        {
            float acc[80];
            gemm_loop<160, 4, 0>(acc, 10, 1, a_sw, b_q, c);
            uint8_t* qs = sm + SM_Q + 2 * w * 128 + g * 16;
            #pragma unroll
            for (int j = 0; j < 20; j++) {
                const int h0 = (8 * j) / 20, d0 = (8 * j) % 20, d = d0 + 2 * t;
                const int off = d < 20 ? h0 * 3072 + (d >> 3) * 1024 + (d & 7) * 2 : (h0 + 1) * 3072 + (d - 20) * 2;
                *(uint32_t*)(qs + off) = pack_bf16(acc[4 * j] * 0.3225964182229561f, acc[4 * j + 1] * 0.3225964182229561f);
                *(uint32_t*)(qs + off + 128) = pack_bf16(acc[4 * j + 2] * 0.3225964182229561f, acc[4 * j + 3] * 0.3225964182229561f);
            }
            asm volatile("fence.proxy.async.shared::cta;" ::: "memory");
            bar_arrive(2, 384);
            bar_arrive(13, 256);
        }
        {
            float acc[112];
            #pragma unroll
            for (int i = 96; i < 112; i++) acc[i] = 0.f;
            #define GEMM_Z(GBX, nkb, first, bd) { if (ct == 3) gemm_loop<192, 4, GBX>(*(float(*)[96])&acc[0], nkb, first, a_sw, bd, c); \
                                                  else gemm_loop<224, 4, GBX>(acc, nkb, first, a_sw, bd, c); }
            GEMM_Z(GB2, 10, 1, b_w)
            uint4* z1p = g_z1 + (size_t)blockIdx.x * 14 * 128 + tid;
            {
                float s0 = 0.f, q0 = 0.f, s1 = 0.f, q1 = 0.f;
                #pragma unroll
                for (int j = 0; j < 14; j++) {
                    float y[8];
                    #pragma unroll
                    for (int i = 0; i < 8; i++) y[i] = gelu2_tanh(acc[8 * j + i]);
                    s0 += (y[0] + y[1]) + (y[4] + y[5]); q0 = fmaf(y[0], y[0], fmaf(y[1], y[1], fmaf(y[4], y[4], fmaf(y[5], y[5], q0))));
                    s1 += (y[2] + y[3]) + (y[6] + y[7]); q1 = fmaf(y[2], y[2], fmaf(y[3], y[3], fmaf(y[6], y[6], fmaf(y[7], y[7], q1))));
                    z1p[(NCTA * 14 + j) * 128] = make_uint4(pack_bf16(y[0], y[1]), pack_bf16(y[2], y[3]), pack_bf16(y[4], y[5]), pack_bf16(y[6], y[7]));
                }
                #pragma unroll
                for (int o = 1; o <= 2; o <<= 1) {
                    s0 += __shfl_xor_sync(0xffffffffu, s0, o); q0 += __shfl_xor_sync(0xffffffffu, q0, o);
                    s1 += __shfl_xor_sync(0xffffffffu, s1, o); q1 += __shfl_xor_sync(0xffffffffu, q1, o);
                }
                if (t < 2) asm volatile("st.relaxed.gpu.global.b64 [%0], %1;" :: "l"(&g_part[(rb * 4 + ct) * 64 + r0 + 8 * t]),
                                        "l"(mkdesc(__float_as_uint(t ? s1 : s0), __float_as_uint(t ? q1 : q0) | 0x80000000u)) : "memory");
            }
            bar_arrive(11, 256);
            GEMM_Z(GB3, 10, 1, b_w)
            #pragma unroll
            for (int j = 0; j < 14; j++)
                z1p[j * 128] = make_uint4(pack_bf16(gelu2_tanh(acc[8 * j]), gelu2_tanh(acc[8 * j + 1])), pack_bf16(gelu2_tanh(acc[8 * j + 2]), gelu2_tanh(acc[8 * j + 3])),
                                          pack_bf16(gelu2_tanh(acc[8 * j + 4]), gelu2_tanh(acc[8 * j + 5])), pack_bf16(gelu2_tanh(acc[8 * j + 6]), gelu2_tanh(acc[8 * j + 7])));
            const float b0 = __bfloat162float(p.bsp[rb * 64 + r0]), b1 = __bfloat162float(p.bsp[rb * 64 + r0 + 8]);
            GEMM_Z(GB4, 32, 1, b_z)
            bar_sync(8, 512);
            const float g0 = 0.5f - 0.5f * s_gate[r0], g1 = 0.5f - 0.5f * s_gate[r0 + 8];
            {
                mbar_wait(c.bar_full + 8 * c.r.st, c.r.ph);
                const uint4* zs = (const uint4*)(sm + SM_G + c.r.st * GST_BYTES) + tid;
                uint8_t* dst = g_hp + (size_t)((rb * 108 + 28 * ct) * 8 + 2 * w) * 128 + g * 16 + t * 4;
                const float e0 = b0 * g0, e1 = b1 * g1;
                #pragma unroll
                for (int j = 0; j < 14; j++) {
                    if (j < 12 || ct < 3) {
                        const uint4 v = zs[j * 128];
                        *(uint32_t*)(dst + (2 * j) * 1024) = pack_bf16(fmaf(acc[8 * j], g0, e0) * bf_lo(v.x), fmaf(acc[8 * j + 1], g0, e0) * bf_hi(v.x));
                        *(uint32_t*)(dst + (2 * j) * 1024 + 128) = pack_bf16(fmaf(acc[8 * j + 2], g1, e1) * bf_lo(v.y), fmaf(acc[8 * j + 3], g1, e1) * bf_hi(v.y));
                        *(uint32_t*)(dst + (2 * j + 1) * 1024) = pack_bf16(fmaf(acc[8 * j + 4], g0, e0) * bf_lo(v.z), fmaf(acc[8 * j + 5], g0, e0) * bf_hi(v.z));
                        *(uint32_t*)(dst + (2 * j + 1) * 1024 + 128) = pack_bf16(fmaf(acc[8 * j + 6], g1, e1) * bf_lo(v.w), fmaf(acc[8 * j + 7], g1, e1) * bf_hi(v.w));
                    }
                }
                __syncwarp();
                if (c.lead) release2(c.bar_empty + 8 * c.r.st, c.peer_off);
                ring_next<GST>(c.r);
            }
            bar_arrive(10, 160);
        }
        {
            float acc[80];
            gemm_loop<160, 4, GB5>(acc, 15, 1, a_t, b_o, c);
            gemm_loop<160, 2, GB5>(acc, 1, 0, a_t, b_o, c);
            gemm_loop<160, 4, GB5>(acc, 4, 0, a_t, b_o, c);
            if (tid < 64) g_part[(rb * 4 + ct) * 64 + tid] = 0ull;
            gemm_loop<160, 4, 0>(acc, 4, 0, a_t, b_o, c);
            uint32_t* os = (uint32_t*)(sm + SM_Q) + r0 * (QS_PITCH / 2) + t;
            #pragma unroll
            for (int j = 0; j < 20; j++) {
                os[4 * j] = pack_bf16(acc[4 * j], acc[4 * j + 1]);
                os[8 * (QS_PITCH / 2) + 4 * j] = pack_bf16(acc[4 * j + 2], acc[4 * j + 3]);
            }
            asm volatile("fence.proxy.async.shared::cta;" ::: "memory");
            __syncwarp();
            if (lane < 16) {
                const int row = 16 * w + lane;
                asm volatile("cp.async.bulk.global.shared::cta.bulk_group [%0], [%1], 320;"
                             :: "l"(p.out + (size_t)(rb * 64 + row) * DM + 160 * ct), "r"(sb + SM_Q + row * (QS_PITCH * 2)) : "memory");
                asm volatile("cp.async.bulk.commit_group;\ncp.async.bulk.wait_group.read 0;" ::: "memory");
            }
            __syncwarp();
            asm volatile("barrier.cluster.arrive.relaxed;\nbarrier.cluster.wait;" ::: "memory");
        }
    } else {
        asm volatile("setmaxnreg.inc.sync.aligned.u32 104;");
        const int atid = threadIdx.x;
        {
            *(uint2*)(sm + SM_Q + 8 * 3072 + (atid & 127) * 8) = make_uint2(0u, 0u);
            if (ct < 3) {
                uint4 w1[2], w2[2];
                const int c1 = blockIdx.x * 67, c2 = blockIdx.x * 90;
                retile_ld<2, 48>(w1, p.wo, DM, 80, 80, c1, 67, atid);
                retile_ld<2, 48>(w2, p.wout, DM, 80, 108, c2, 90, atid);
                retile_st<20, 2, 48, true>(w1, 80, 80, g_wot, c1, 67, atid);
                retile_st<20, 2, 48, false>(w2, 80, 108, g_woutt, c2, 90, atid);
                bar_sync(9, 384);
                if (atid == 256) flag_add(F_WR);
            } else {
                mbar_wait(bar_kfull + 48, 0);
                #pragma unroll 2
                for (int e = atid; e < 1280; e += 384) {
                    const int m = e >= 640, k = e - m * 640;
                    const uint2* src = (const uint2*)(sm + SM_W + e * 40);
                    const uint2 a = src[0], b = src[1], c = src[2], d = src[3], f = src[4];
                    const uint32_t gt = m ? *(const unsigned short*)(sm + SM_W + 51200 + k * 2) : 0u;
                    uint4* dst = (uint4*)(sm + SM_KV + (k >> 3) * 768 + (k & 7) * 16 + m * 384);
                    dst[0] = make_uint4(a.x, a.y, b.x, b.y); dst[8] = make_uint4(c.x, c.y, d.x, d.y); dst[16] = make_uint4(f.x, f.y, 0u, gt);
                }
                asm volatile("fence.proxy.async.shared::cta;" ::: "memory");
                bar_arrive(1, 512);
            }
        }
        const uint32_t half2c = *(const volatile uint32_t*)&g_const[0];
        if (wg == 2) {
            const int r0 = 16 * w + g;
            uint4* z1p = g_z1 + (size_t)blockIdx.x * 14 * 128 + tid;
            uint4 v[14];
            bar_sync(11, 256);
            #pragma unroll
            for (int j = 0; j < 14; j++) v[j] = __ldcg(z1p + (NCTA * 14 + j) * 128);
            float s0, q0, s1, q1;
            {
                unsigned long long a, b;
                const unsigned long long* pa_ = &g_part[(rb * 4 + t) * 64 + r0];
                #pragma unroll 1
                for (int it = 0; ; it++) {
                    asm volatile("ld.relaxed.gpu.global.b64 %0, [%1];" : "=l"(a) : "l"(pa_) : "memory");
                    asm volatile("ld.relaxed.gpu.global.b64 %0, [%1];" : "=l"(b) : "l"(pa_ + 8) : "memory");
                    if (__all_sync(0xffffffffu, ((a & b) >> 63) != 0)) break;
                    if (it > SPIN_LIMIT) SPIN_FAIL(0x7000);
                    __nanosleep(100);
                }
                s0 = __uint_as_float((uint32_t)a); q0 = __uint_as_float((uint32_t)(a >> 32) & 0x7FFFFFFFu);
                s1 = __uint_as_float((uint32_t)b); q1 = __uint_as_float((uint32_t)(b >> 32) & 0x7FFFFFFFu);
                #pragma unroll
                for (int o = 1; o <= 2; o <<= 1) {
                    s0 += __shfl_xor_sync(0xffffffffu, s0, o); q0 += __shfl_xor_sync(0xffffffffu, q0, o);
                    s1 += __shfl_xor_sync(0xffffffffu, s1, o); q1 += __shfl_xor_sync(0xffffffffu, q1, o);
                }
            }
            const float m0 = s0 * (1.f / FH), m1 = s1 * (1.f / FH);
            const float rs0 = rsqrtf(fmaxf(q0 * (1.f / FH) - m0 * m0, 0.f) + 4e-5f), rs1 = rsqrtf(fmaxf(q1 * (1.f / FH) - m1 * m1, 0.f) + 4e-5f);
            const float c0 = -m0 * rs0, c1 = -m1 * rs1;
            uint8_t* dst = g_z2n + (size_t)(ct * 32 + rb) * 28672 + (2 * w) * 3584 + g * 16 + t * 4;
            #pragma unroll
            for (int j = 0; j < 14; j++) {
                *(uint32_t*)(dst + 2 * j * 128) = pack_bf16(fmaf(bf_lo(v[j].x), rs0, c0), fmaf(bf_hi(v[j].x), rs0, c0));
                *(uint32_t*)(dst + 3584 + 2 * j * 128) = pack_bf16(fmaf(bf_lo(v[j].y), rs1, c1), fmaf(bf_hi(v[j].y), rs1, c1));
                *(uint32_t*)(dst + (2 * j + 1) * 128) = pack_bf16(fmaf(bf_lo(v[j].z), rs0, c0), fmaf(bf_hi(v[j].z), rs0, c0));
                *(uint32_t*)(dst + 3584 + (2 * j + 1) * 128) = pack_bf16(fmaf(bf_lo(v[j].w), rs1, c1), fmaf(bf_hi(v[j].w), rs1, c1));
            }
            bar_sync(6, 128);
            if (tid == 0) flag_add(F_Z2 + rb * 4 + ct);
        }
        if (wg == 2) bar_sync(13, 256); else bar_sync(2, 384);
        const int p0 = wg == 2 ? 1 : 0;
        #define HEAD(ps) ((ps) == 0 ? wg : 3 * (ps) - 1 + wg)
        uint32_t qmax2 = 0;
        #pragma unroll 1
        for (int i = p0 + (tid >> 6); i < 3; i += 2) {
            uint8_t* qrow = sm + SM_Q + HEAD(i) * 3072 + (tid & 63) * 16;
            const uint4 a = *(const uint4*)qrow, b = *(const uint4*)(qrow + 1024);
            const uint2 c = *(const uint2*)(qrow + 2048);
            #define SQ(v) (bf_lo(v) * bf_lo(v) + bf_hi(v) * bf_hi(v))
            const float n = SQ(a.x) + SQ(a.y) + SQ(a.z) + SQ(a.w) + SQ(b.x) + SQ(b.y) + SQ(b.z) + SQ(b.w) + SQ(c.x) + SQ(c.y);
            qmax2 = max(qmax2, __float_as_uint(n) & 0x7FFFFFFFu);
            *(uint2*)(qrow + 2048 + 8) = make_uint2(0x3F803F80u, 0u);
        }
        asm volatile("fence.proxy.async.shared::cta;" ::: "memory");
        mbar_sleep(bar_kfull + 32, 0);
        bar_arrive(8, 512);
        uint32_t safe;
        {
            const float kmax2 = __uint_as_float(__reduce_max_sync(0xffffffffu, __float_as_uint(s_stat[lane])));
            const int ev = (int)(__reduce_max_sync(0xffffffffu, __float_as_uint(s_stat[32 + lane])) >> 23) - 126;
            const float bmax = (float)min(102 - max(ev, 1), 100 + ev);
            const bool ok = bmax > 0.f && __uint_as_float(qmax2) * kmax2 <= bmax * bmax;
            asm volatile("{\n.reg .pred p, q;\nsetp.ne.u32 p, %1, 0;\nbarrier.red.and.pred.aligned q, %2, 128, p;\nselp.u32 %0, 1, 0, q;\n}"
                         : "=r"(safe) : "r"((uint32_t)ok), "r"(4 + wg) : "memory");
            safe = __shfl_sync(0xffffffffu, safe, 0);
            if (!safe) {
                #pragma unroll 1
                for (int i = p0 + (tid >> 6); i < 3; i += 2) *(uint2*)(sm + SM_Q + HEAD(i) * 3072 + (tid & 63) * 16 + 2048 + 8) = make_uint2(0u, 0u);
                asm volatile("fence.proxy.async.shared::cta;" ::: "memory");
                bar_sync(4 + wg, 128);
            }
        }
        const uint32_t kv16 = ((sb + SM_KV) & 0x3FFFFu) >> 4;
        constexpr uint32_t KLBO = 8u << 16, KHI = 24u, VLBO = (24u << 16) + 192u, VHI = 8u;
        const bool lead = lane == 0;
        const int r0 = 16 * w + g;
        static_assert(KST == 4, "ring phases below assume 4 stages");
        if (wg == 2) {
            bar_sync(14, 256);
            mbar_wait(bar_kfull + 24, 1);
        }
        const uint32_t q16 = ((sb + SM_Q) & 0x3FFFFu) >> 4;
        uint64_t qa = mkdesc(q16 + HEAD(p0) * 192 + (64u << 16), 8), qb = mkdesc(q16 + HEAD(p0) * 192 + 128 + ((uint32_t)(1536 - 128 - HEAD(p0) * 192) << 16), 8);
        #define NEXT_HEAD(ps) { const uint32_t d_ = (ps) == 0 ? 384 : 576; qa += d_; qb += (uint64_t)d_ - ((uint64_t)d_ << 16); }
        const uint64_t dk = mkdesc(kv16 + KLBO, KHI), dv = mkdesc(kv16 + VLBO, VHI);
        const uint32_t kep = bar_kempty + peer_off;
        uint32_t rc = lead ? (wg == 0 ? 2 : 1) : 0;
        float o[12];
        #pragma unroll
        for (int i = 0; i < 12; i++) o[i] = 0.f;
        float s[32]; uint32_t pa[16], pb[16];
        FENCE_F(o, 12);
        #define QK(off) wgmma_ss_n64<0, 0>(s, qa, dk + (off), 0); wgmma_ss_n64<0, 0>(s, qb, dk + (off) + 16, 1);
        #define PV(pp, off) wgmma_rs_n24<1>(o, pp[0], pp[1], pp[2], pp[3], dv + (off), 1); wgmma_rs_n24<1>(o, pp[4], pp[5], pp[6], pp[7], dv + (off) + 48, 1); \
                            wgmma_rs_n24<1>(o, pp[8], pp[9], pp[10], pp[11], dv + (off) + 96, 1); wgmma_rs_n24<1>(o, pp[12], pp[13], pp[14], pp[15], dv + (off) + 144, 1);
        #define STORE_O(h) { \
            const float l0 = __shfl_sync(0xffffffffu, o[8], (lane & ~3) | 2), l1 = __shfl_sync(0xffffffffu, o[10], (lane & ~3) | 2); \
            const float i0 = __fdividef(s_gate[r0], l0), i1 = __fdividef(s_gate[r0 + 8], l1);        \
            _Pragma("unroll") for (int b = 0; b < 3; b++) { \
                if (b < 2 || t < 2) { \
                    const int cq = 20 * (h) + 8 * b + 2 * t, col = cq < 32 ? ct * 32 + cq : (cq < 96 ? 96 + ct * 64 + cq : 288 + ct * 64 + cq); \
                    uint8_t* dst = g_op + (size_t)((rb * 80 + (col >> 3)) * 8 + 2 * w) * 128 + g * 16 + (col & 7) * 2; \
                    *(uint32_t*)dst = pack_bf16(o[4 * b] * i0, o[4 * b + 1] * i0); \
                    *(uint32_t*)(dst + 128) = pack_bf16(o[4 * b + 2] * i1, o[4 * b + 3] * i1); \
                } \
            } \
            _Pragma("unroll") for (int i = 0; i < 12; i++) o[i] = 0.f; \
            FENCE_F(o, 12); \
 \
            __syncwarp(); }
        if (safe) {
            wg_fence();
            QK(3 * 768 + 384)
            wg_commit();
            wg_wait<0>();
            FENCE_F(s, 32);
            release2n(bar_kempty + 24, kep + 24, rc);
            EXPBLK(pa, s);
            FENCE_R(pa, 16);
            #define HALF(off, pin, pout) \
                wg_fence(); \
                QK(off) \
                wg_commit(); \
                PV(pin, off) \
                wg_commit(); \
                wg_wait<1>(); \
                FENCE_F(s, 32); \
                EXPBLK(pout, s); \
                FENCE_R(pout, 16); \
                wg_wait<0>();
            #pragma unroll 1
            for (int J4 = 4 * p0; J4 < 12; J4++) {
                const uint32_t ph = J4 & 1;
                #pragma unroll
                for (int st = 0; st < 4; st++) {
                    mbar_wait(bar_kfull + 8 * st, ph);
                    if (st == 3 && J4 == 3 && wg == 0) bar_arrive(14, 256);
                    HALF(st * 768, pa, pb)
                    if (st == 3 && (J4 & 3) == 3 && J4 < 11) NEXT_HEAD(J4 >> 2)
                    HALF(st * 768 + 384, pb, pa)
                    if (st < 3) release2n(bar_kempty + 8 * st, kep + 8 * st, rc);
                }
                if ((J4 & 3) == 3) {
                    FENCE_F(o, 12);
                    STORE_O(HEAD(J4 >> 2))
                    rc = lead ? 1 : 0;
                }
                release2n(bar_kempty + 24, kep + 24, rc);
            }
        } else {
            float m0 = -INFINITY, m1 = -INFINITY;
            #pragma unroll 1
            for (int u = 32 * p0; u < 96; u++) {
                const int J = u >> 1;
                if ((u & 1) == 0) mbar_wait(bar_kfull + 8 * (J & 3), (J >> 2) & 1);
                if (u == 30 && wg == 0) bar_arrive(14, 256);
                wg_fence();
                QK(((u + 7) & 7) * 384)
                wg_commit();
                wg_wait<0>();
                FENCE_F(s, 32);
                float x0 = m0, x1 = m1;
                #pragma unroll
                for (int b = 0; b < 8; b++) {
                    const float f = ((PAT >> b) & 1) ? 0.5f : 1.f;
                    s[4 * b] *= f; s[4 * b + 1] *= f; s[4 * b + 2] *= f; s[4 * b + 3] *= f;
                    x0 = fmaxf(x0, fmaxf(s[4 * b], s[4 * b + 1])); x1 = fmaxf(x1, fmaxf(s[4 * b + 2], s[4 * b + 3]));
                }
                x0 = fmaxf(x0, __shfl_xor_sync(0xffffffffu, x0, 1)); x0 = fmaxf(x0, __shfl_xor_sync(0xffffffffu, x0, 2));
                x1 = fmaxf(x1, __shfl_xor_sync(0xffffffffu, x1, 1)); x1 = fmaxf(x1, __shfl_xor_sync(0xffffffffu, x1, 2));
                const float f0 = exp2f(m0 - x0), f1 = exp2f(m1 - x1);
                m0 = x0; m1 = x1;
                #pragma unroll
                for (int b = 0; b < 3; b++) { o[4 * b] *= f0; o[4 * b + 1] *= f0; o[4 * b + 2] *= f1; o[4 * b + 3] *= f1; }
                #pragma unroll
                for (int b = 0; b < 8; b++) {
                    pa[2 * b] = exp2_mufu(s[4 * b] - m0, s[4 * b + 1] - m0);
                    pa[2 * b + 1] = exp2_mufu(s[4 * b + 2] - m1, s[4 * b + 3] - m1);
                }
                FENCE_R(pa, 16); FENCE_F(o, 12);
                wg_fence();
                PV(pa, (u & 7) * 384)
                wg_commit();
                wg_wait<0>();
                FENCE_F(o, 12);
                if ((u & 1) == 0) release2n(bar_kempty + 8 * ((J + 3) & 3), kep + 8 * ((J + 3) & 3), rc);
                if ((u & 31) == 31) {
                    STORE_O(HEAD(u >> 5))
                    m0 = -INFINITY; m1 = -INFINITY;
                    NEXT_HEAD(u >> 5)
                    rc = lead ? 1 : 0;
                }
            }
        }
        bar_sync(4 + wg, 128);
        if (tid == 0) flag_add(F_O + rb * 3 + 2);
    }
}

typedef CUresult (*EncodeFn)(CUtensorMap*, CUtensorMapDataType, cuuint32_t, void*, const cuuint64_t*, const cuuint64_t*, const cuuint32_t*,
                             const cuuint32_t*, CUtensorMapInterleave, CUtensorMapSwizzle, CUtensorMapL2promotion, CUtensorMapFloatOOBfill);

void make_map(EncodeFn fn, CUtensorMap* m, const void* ptr, uint64_t cols, uint64_t rows, uint32_t bc, uint32_t br, CUtensorMapSwizzle sw) {
    cuuint64_t dims[2] = {cols, rows}, strides[1] = {cols * 2};
    cuuint32_t box[2] = {bc, br}, es[2] = {1, 1};
    fn(m, CU_TENSOR_MAP_DATA_TYPE_BFLOAT16, 2, const_cast<void*>(ptr), dims, strides, box, es, CU_TENSOR_MAP_INTERLEAVE_NONE, sw,
       CU_TENSOR_MAP_L2_PROMOTION_L2_128B, CU_TENSOR_MAP_FLOAT_OOB_FILL_NONE);
}

void make_map3(EncodeFn fn, CUtensorMap* m, const void* ptr, uint64_t cols, uint64_t rows, uint32_t natoms) {
    cuuint64_t dims[3] = {32, rows, cols / 32}, strides[2] = {cols * 2, 64};
    cuuint32_t box[3] = {32, 32, natoms}, es[3] = {1, 1, 1};
    fn(m, CU_TENSOR_MAP_DATA_TYPE_BFLOAT16, 3, const_cast<void*>(ptr), dims, strides, box, es, CU_TENSOR_MAP_INTERLEAVE_NONE, CU_TENSOR_MAP_SWIZZLE_64B,
       CU_TENSOR_MAP_L2_PROMOTION_L2_128B, CU_TENSOR_MAP_FLOAT_OOB_FILL_NONE);
}

}

extern "C" void kernel_launch(void* const* d_in, const int* in_sizes, int n_in, void* d_out, int out_size) {
    static EncodeFn fn = nullptr;
    if (!fn) {
        cudaDriverEntryPointQueryResult qr;
        void* f = nullptr;
        cudaGetDriverEntryPoint("cuTensorMapEncodeTiled", &f, cudaEnableDefault, &qr);
        fn = (EncodeFn)f;
        cudaFuncSetAttribute(mega_kernel, cudaFuncAttributeMaxDynamicSharedMemorySize, SM_TOTAL);
    }
    Params p;
    const __nv_bfloat16* x = (const __nv_bfloat16*)d_in[0];
    make_map(fn, &p.mx, x, DM, S_LEN, 64, 64, CU_TENSOR_MAP_SWIZZLE_128B);
    make_map(fn, &p.mwsp, d_in[7], S_LEN, S_LEN, 64, 64, CU_TENSOR_MAP_SWIZZLE_128B);
    make_map3(fn, &p.mwq, d_in[1], DM, DM, 5);
    make_map3(fn, &p.mwin, d_in[6], 2 * FH, DM, 7);
    p.wq = (const __nv_bfloat16*)d_in[1];
    p.win = (const __nv_bfloat16*)d_in[6];
    p.wk = (const __nv_bfloat16*)d_in[2];
    p.wv = (const __nv_bfloat16*)d_in[3];
    p.bsp = (const __nv_bfloat16*)d_in[8];
    p.gw = (const __nv_bfloat16*)d_in[10];
    p.wo = (const __nv_bfloat16*)d_in[4];
    p.wout = (const __nv_bfloat16*)d_in[9];
    p.out = (__nv_bfloat16*)d_out;
    mega_kernel<<<NCTA, 640, SM_TOTAL>>>(p);
}
```

```cpp
#include <cuda_runtime.h>
#include <cuda_bf16.h>
#include <cuda.h>
#include <stdint.h>

namespace {

constexpr int S_LEN = 2048, DM = 640, FH = 864;
constexpr int NCTA = 128;
#define PAT8 0xB5u
constexpr uint32_t PAT = PAT8 * 0x101u;
#define GB2 -1
#define GB3 -1
#define GB4 2
#define GB5 -1
constexpr int GST = 4;
constexpr int GST_BYTES = 36864;
constexpr int KST = 4;
constexpr int KST_BYTES = 12288;
constexpr int QS_PITCH = 168;
constexpr int SM_G = 0;
constexpr int SM_KV = SM_G + GST * GST_BYTES;
constexpr int SM_Q = SM_KV + KST * KST_BYTES;
constexpr int SM_MISC = SM_Q + 8 * 3072 + 1024;
constexpr int SM_W = SM_G + 2 * GST_BYTES + 16384;
constexpr int SM_TOTAL = SM_MISC + 2048 + 1024;

constexpr int F_KV = 0, F_DONE = 1, F_WR = 2, F_Z2 = 3, F_H = F_Z2 + 128, F_O = F_H + 32, F_NUM = F_O + 96;

__device__ __align__(1024) uint8_t g_kv[16 * KST_BYTES];
__device__ __align__(1024) uint8_t g_z2n[4 * 32 * 28672];
__device__ __align__(1024) uint8_t g_hp[32 * 108 * 1024];
__device__ __align__(1024) uint8_t g_op[32 * 80 * 1024];
__device__ __align__(1024) uint8_t g_wot[4 * 80 * 2560];
__device__ __align__(1024) uint8_t g_woutt[4 * 108 * 2560];
__device__ __align__(1024) uint4 g_z1[2 * NCTA * 14 * 128];
__device__ unsigned long long g_part[32 * 4 * 64];
__device__ __align__(128) float g_kvmax[64];
__device__ __align__(128) float g_gate[S_LEN];
__device__ unsigned g_flags[F_NUM * 8];
__device__ uint32_t g_const[1] = {0x3F013F01u};

struct Params {
    CUtensorMap mx, mwsp, mwq, mwin;
    const __nv_bfloat16 *wk, *wv, *bsp, *gw, *wo, *wout, *wq, *win;
    __nv_bfloat16* out;
};

template<int TB> __device__ __forceinline__ void wgmma_rs_n24(float (&d)[12], uint32_t a0, uint32_t a1, uint32_t a2, uint32_t a3, uint64_t db, int scale_d) {
  asm volatile("{\n.reg .pred p;\nsetp.ne.b32 p, %17, 0;\nwgmma.mma_async.sync.aligned.m64n24k16.f32.bf16.bf16 {%0,%1,%2,%3,%4,%5,%6,%7,%8,%9,%10,%11}, {%12,%13,%14,%15}, %16, p, 1, 1, %18;\n}"
    : "+f"(d[0]), "+f"(d[1]), "+f"(d[2]), "+f"(d[3]), "+f"(d[4]), "+f"(d[5]), "+f"(d[6]), "+f"(d[7]), "+f"(d[8]), "+f"(d[9]), "+f"(d[10]), "+f"(d[11])
    : "r"(a0), "r"(a1), "r"(a2), "r"(a3), "l"(db), "r"(scale_d), "n"(TB));
}
template<int TA, int TB> __device__ __forceinline__ void wgmma_ss_n48(float (&d)[24], uint64_t da, uint64_t db, int scale_d) {
  asm volatile("{\n.reg .pred p;\nsetp.ne.b32 p, %26, 0;\nwgmma.mma_async.sync.aligned.m64n48k16.f32.bf16.bf16 {%0,%1,%2,%3,%4,%5,%6,%7,%8,%9,%10,%11,%12,%13,%14,%15,%16,%17,%18,%19,%20,%21,%22,%23}, %24, %25, p, 1, 1, %27, %28;\n}"
    : "+f"(d[0]), "+f"(d[1]), "+f"(d[2]), "+f"(d[3]), "+f"(d[4]), "+f"(d[5]), "+f"(d[6]), "+f"(d[7]), "+f"(d[8]), "+f"(d[9]), "+f"(d[10]), "+f"(d[11]), "+f"(d[12]), "+f"(d[13]), "+f"(d[14]), "+f"(d[15]), "+f"(d[16]), "+f"(d[17]), "+f"(d[18]), "+f"(d[19]), "+f"(d[20]), "+f"(d[21]), "+f"(d[22]), "+f"(d[23])
    : "l"(da), "l"(db), "r"(scale_d), "n"(TA), "n"(TB));
}
template<int TA, int TB> __device__ __forceinline__ void wgmma_ss_n64(float (&d)[32], uint64_t da, uint64_t db, int scale_d) {
  asm volatile("{\n.reg .pred p;\nsetp.ne.b32 p, %34, 0;\nwgmma.mma_async.sync.aligned.m64n64k16.f32.bf16.bf16 {%0,%1,%2,%3,%4,%5,%6,%7,%8,%9,%10,%11,%12,%13,%14,%15,%16,%17,%18,%19,%20,%21,%22,%23,%24,%25,%26,%27,%28,%29,%30,%31}, %32, %33, p, 1, 1, %35, %36;\n}"
    : "+f"(d[0]), "+f"(d[1]), "+f"(d[2]), "+f"(d[3]), "+f"(d[4]), "+f"(d[5]), "+f"(d[6]), "+f"(d[7]), "+f"(d[8]), "+f"(d[9]), "+f"(d[10]), "+f"(d[11]), "+f"(d[12]), "+f"(d[13]), "+f"(d[14]), "+f"(d[15]), "+f"(d[16]), "+f"(d[17]), "+f"(d[18]), "+f"(d[19]), "+f"(d[20]), "+f"(d[21]), "+f"(d[22]), "+f"(d[23]), "+f"(d[24]), "+f"(d[25]), "+f"(d[26]), "+f"(d[27]), "+f"(d[28]), "+f"(d[29]), "+f"(d[30]), "+f"(d[31])
    : "l"(da), "l"(db), "r"(scale_d), "n"(TA), "n"(TB));
}
template<int TA, int TB> __device__ __forceinline__ void wgmma_ss_n96(float (&d)[48], uint64_t da, uint64_t db, int scale_d) {
  asm volatile("{\n.reg .pred p;\nsetp.ne.b32 p, %50, 0;\nwgmma.mma_async.sync.aligned.m64n96k16.f32.bf16.bf16 {%0,%1,%2,%3,%4,%5,%6,%7,%8,%9,%10,%11,%12,%13,%14,%15,%16,%17,%18,%19,%20,%21,%22,%23,%24,%25,%26,%27,%28,%29,%30,%31,%32,%33,%34,%35,%36,%37,%38,%39,%40,%41,%42,%43,%44,%45,%46,%47}, %48, %49, p, 1, 1, %51, %52;\n}"
    : "+f"(d[0]), "+f"(d[1]), "+f"(d[2]), "+f"(d[3]), "+f"(d[4]), "+f"(d[5]), "+f"(d[6]), "+f"(d[7]), "+f"(d[8]), "+f"(d[9]), "+f"(d[10]), "+f"(d[11]), "+f"(d[12]), "+f"(d[13]), "+f"(d[14]), "+f"(d[15]), "+f"(d[16]), "+f"(d[17]), "+f"(d[18]), "+f"(d[19]), "+f"(d[20]), "+f"(d[21]), "+f"(d[22]), "+f"(d[23]), "+f"(d[24]), "+f"(d[25]), "+f"(d[26]), "+f"(d[27]), "+f"(d[28]), "+f"(d[29]), "+f"(d[30]), "+f"(d[31]), "+f"(d[32]), "+f"(d[33]), "+f"(d[34]), "+f"(d[35]), "+f"(d[36]), "+f"(d[37]), "+f"(d[38]), "+f"(d[39]), "+f"(d[40]), "+f"(d[41]), "+f"(d[42]), "+f"(d[43]), "+f"(d[44]), "+f"(d[45]), "+f"(d[46]), "+f"(d[47])
    : "l"(da), "l"(db), "r"(scale_d), "n"(TA), "n"(TB));
}
template<int TA, int TB> __device__ __forceinline__ void wgmma_ss_n128(float (&d)[64], uint64_t da, uint64_t db, int scale_d) {
  asm volatile("{\n.reg .pred p;\nsetp.ne.b32 p, %66, 0;\nwgmma.mma_async.sync.aligned.m64n128k16.f32.bf16.bf16 {%0,%1,%2,%3,%4,%5,%6,%7,%8,%9,%10,%11,%12,%13,%14,%15,%16,%17,%18,%19,%20,%21,%22,%23,%24,%25,%26,%27,%28,%29,%30,%31,%32,%33,%34,%35,%36,%37,%38,%39,%40,%41,%42,%43,%44,%45,%46,%47,%48,%49,%50,%51,%52,%53,%54,%55,%56,%57,%58,%59,%60,%61,%62,%63}, %64, %65, p, 1, 1, %67, %68;\n}"
    : "+f"(d[0]), "+f"(d[1]), "+f"(d[2]), "+f"(d[3]), "+f"(d[4]), "+f"(d[5]), "+f"(d[6]), "+f"(d[7]), "+f"(d[8]), "+f"(d[9]), "+f"(d[10]), "+f"(d[11]), "+f"(d[12]), "+f"(d[13]), "+f"(d[14]), "+f"(d[15]), "+f"(d[16]), "+f"(d[17]), "+f"(d[18]), "+f"(d[19]), "+f"(d[20]), "+f"(d[21]), "+f"(d[22]), "+f"(d[23]), "+f"(d[24]), "+f"(d[25]), "+f"(d[26]), "+f"(d[27]), "+f"(d[28]), "+f"(d[29]), "+f"(d[30]), "+f"(d[31]), "+f"(d[32]), "+f"(d[33]), "+f"(d[34]), "+f"(d[35]), "+f"(d[36]), "+f"(d[37]), "+f"(d[38]), "+f"(d[39]), "+f"(d[40]), "+f"(d[41]), "+f"(d[42]), "+f"(d[43]), "+f"(d[44]), "+f"(d[45]), "+f"(d[46]), "+f"(d[47]), "+f"(d[48]), "+f"(d[49]), "+f"(d[50]), "+f"(d[51]), "+f"(d[52]), "+f"(d[53]), "+f"(d[54]), "+f"(d[55]), "+f"(d[56]), "+f"(d[57]), "+f"(d[58]), "+f"(d[59]), "+f"(d[60]), "+f"(d[61]), "+f"(d[62]), "+f"(d[63])
    : "l"(da), "l"(db), "r"(scale_d), "n"(TA), "n"(TB));
}

__device__ __forceinline__ uint64_t mkdesc(uint32_t lo, uint32_t hi) { uint64_t d; asm("mov.b64 %0, {%1, %2};" : "=l"(d) : "r"(lo), "r"(hi)); return d; }
__device__ __forceinline__ void mbar_init(uint32_t a, int c) { asm volatile("mbarrier.init.shared::cta.b64 [%0], %1;" :: "r"(a), "r"(c)); }
__device__ __forceinline__ void mbar_expect(uint32_t a, uint32_t b) { asm volatile("mbarrier.arrive.expect_tx.shared::cta.b64 _, [%0], %1;" :: "r"(a), "r"(b) : "memory"); }
__device__ __forceinline__ void mbar_arrive(uint32_t a) { asm volatile("mbarrier.arrive.shared::cta.b64 _, [%0];" :: "r"(a) : "memory"); }
#define SPIN_LIMIT (1 << 20)
#define SPIN_FAIL(code) __trap()
__device__ __forceinline__ void mbar_wait(uint32_t a, uint32_t ph) {
    asm volatile("{\n.reg .pred p, q;\n.reg .u32 c;\nmov.u32 c, 0;\n"
                 "W0:\nmbarrier.try_wait.parity.shared::cta.b64 p, [%0], %1;\n@p bra W1;\n"
                 "add.u32 c, c, 1;\nsetp.lt.u32 q, c, %2;\n@q bra W0;\ntrap;\n"
                 "W1:\n}" :: "r"(a), "r"(ph), "n"(4 * SPIN_LIMIT) : "memory");
}
__device__ __forceinline__ void mbar_sleep(uint32_t a, uint32_t ph) {
    asm volatile("{\n.reg .pred p, q;\n.reg .u32 c;\nmov.u32 c, 0;\n"
                 "W0:\nmbarrier.try_wait.parity.shared::cta.b64 p, [%0], %1, 4000;\n@p bra W1;\n"
                 "add.u32 c, c, 1;\nsetp.lt.u32 q, c, %2;\n@q bra W0;\ntrap;\n"
                 "W1:\n}" :: "r"(a), "r"(ph), "n"(SPIN_LIMIT) : "memory");
}
__device__ __forceinline__ void wg_fence() { asm volatile("wgmma.fence.sync.aligned;" ::: "memory"); }
__device__ __forceinline__ void wg_commit() { asm volatile("wgmma.commit_group.sync.aligned;" ::: "memory"); }
template<int N> __device__ __forceinline__ void wg_wait() { asm volatile("wgmma.wait_group.sync.aligned %0;" :: "n"(N) : "memory"); }
__device__ __forceinline__ void bar_sync(int id, int n) { asm volatile("bar.sync %0, %1;" :: "r"(id), "r"(n) : "memory"); }
__device__ __forceinline__ void bar_arrive(int id, int n) { asm volatile("bar.arrive %0, %1;" :: "r"(id), "r"(n) : "memory"); }
__device__ __forceinline__ void fence_async() { asm volatile("fence.proxy.async.global;" ::: "memory"); }
__device__ __forceinline__ void flag_wait(int f, unsigned target) {
    const unsigned* p = &g_flags[f * 8];
    unsigned v;
    #pragma unroll 1
    for (int it = 0; it < SPIN_LIMIT; it++) {
        asm volatile("ld.acquire.gpu.global.u32 %0, [%1];" : "=r"(v) : "l"(p) : "memory");
        if (v >= target) return;
        __nanosleep(20);
    }
    SPIN_FAIL(f);
}
__device__ __forceinline__ void flag_add(int f) { asm volatile("red.release.gpu.global.add.u32 [%0], 1;" :: "l"(&g_flags[f * 8]) : "memory"); }
__device__ __forceinline__ void tma2d(uint32_t dst, const CUtensorMap* m, int c0, int c1, uint32_t bar) {
    asm volatile("cp.async.bulk.tensor.2d.shared::cluster.global.mbarrier::complete_tx::bytes [%0], [%1, {%3, %4}], [%2];"
        :: "r"(dst), "l"(m), "r"(bar), "r"(c0), "r"(c1) : "memory");
}
__device__ __forceinline__ void bulk_ld(uint32_t dst, const void* src, uint32_t bytes, uint32_t bar) {
    asm volatile("cp.async.bulk.shared::cluster.global.mbarrier::complete_tx::bytes [%0], [%1], %2, [%3];"
        :: "r"(dst), "l"(src), "r"(bytes), "r"(bar) : "memory");
}
__device__ __forceinline__ void tma3d_mc(uint32_t dst, const CUtensorMap* m, int c1, int c2, uint32_t bar) {
    asm volatile("cp.async.bulk.tensor.3d.shared::cluster.global.mbarrier::complete_tx::bytes.multicast::cluster [%0], [%1, {0, %3, %4}], [%2], %5;"
        :: "r"(dst), "l"(m), "r"(bar), "r"(c1), "r"(c2), "h"((uint16_t)3) : "memory");
}
__device__ __forceinline__ void bulk_ld_mc(uint32_t dst, const void* src, uint32_t bytes, uint32_t bar) {
    asm volatile("cp.async.bulk.shared::cluster.global.mbarrier::complete_tx::bytes.multicast::cluster [%0], [%1], %2, [%3], %4;"
        :: "r"(dst), "l"(src), "r"(bytes), "r"(bar), "h"((uint16_t)3) : "memory");
}
__device__ __forceinline__ void release2(uint32_t a, uint32_t peer_off) {
    asm volatile("mbarrier.arrive.shared::cta.b64 _, [%0];\nmbarrier.arrive.shared::cluster.b64 _, [%1];" :: "r"(a), "r"(a + peer_off) : "memory");
}
__device__ __forceinline__ void release2n(uint32_t a, uint32_t pa, uint32_t cnt) {
    asm volatile("{\n.reg .pred p;\nsetp.ne.u32 p, %2, 0;\n@p mbarrier.arrive.shared::cta.b64 _, [%0], %2;\n@p mbarrier.arrive.shared::cluster.b64 _, [%1], %2;\n}"
                 :: "r"(a), "r"(pa), "r"(cnt) : "memory");
}
__device__ __forceinline__ bool elect_one() {
    uint32_t p;
    asm volatile("{\n.reg .pred q;\nelect.sync _|q, 0xffffffff;\nselp.u32 %0, 1, 0, q;\n}" : "=r"(p));
    return p != 0;
}
__device__ __forceinline__ void l2_prefetch(const void* src, uint32_t bytes) {
    asm volatile("cp.async.bulk.prefetch.L2.global [%0], %1;" :: "l"(src), "r"(bytes) : "memory");
}
__device__ __forceinline__ uint32_t pack_bf16(float lo, float hi) { uint32_t r; asm("cvt.rn.bf16x2.f32 %0, %1, %2;" : "=r"(r) : "f"(hi), "f"(lo)); return r; }
__device__ __forceinline__ float bf_lo(uint32_t v) { return __uint_as_float(v << 16); }
__device__ __forceinline__ float bf_hi(uint32_t v) { return __uint_as_float(v & 0xFFFF0000u); }
__device__ __forceinline__ float gelu2_tanh(float x) {
    float u = x * fmaf(x * x, 0.0356774081363001f, 0.7978845608028654f), t;
    asm("tanh.approx.f32 %0, %1;" : "=f"(t) : "f"(u));
    return fmaf(x, t, x);
}
#define FENCE_F(a, n) _Pragma("unroll") for (int i_ = 0; i_ < n; i_++) asm volatile("" : "+f"(a[i_]) :: "memory");
#define FENCE_R(a, n) _Pragma("unroll") for (int i_ = 0; i_ < n; i_++) asm volatile("" : "+r"(a[i_]) :: "memory");

__device__ __forceinline__ uint32_t exp2_mufu(float a, float b) {
    float x, y;
    asm("ex2.approx.ftz.f32 %0, %1;" : "=f"(x) : "f"(a));
    asm("ex2.approx.ftz.f32 %0, %1;" : "=f"(y) : "f"(b));
    return pack_bf16(x, y);
}
__device__ __forceinline__ uint32_t exp2_alu(float a, float b, uint32_t half2c) {
    uint32_t L = __byte_perm(__float_as_uint(a), __float_as_uint(b), 0x6521), G, E, r;
    asm("lop3.b32 %0, %1, 0x007F007F, %2, 0xE2;" : "=r"(G) : "r"(L), "r"(half2c));
    asm("lop3.b32 %0, %1, 0x007F007F, %2, 0xB8;" : "=r"(E) : "r"(L), "r"(half2c));
    asm("fma.rn.bf16x2 %0, %1, %2, %3;" : "=r"(r) : "r"(G), "r"(L), "r"(E));
    return r;
}
#define EXPBLK(p, s) _Pragma("unroll") for (int b = 0; b < 8; b++) { \
    if ((PAT >> b) & 1) { p[2*b] = exp2_alu(s[4*b], s[4*b+1], half2c); p[2*b+1] = exp2_alu(s[4*b+2], s[4*b+3], half2c); } \
    else { p[2*b] = exp2_mufu(s[4*b], s[4*b+1]); p[2*b+1] = exp2_mufu(s[4*b+2], s[4*b+3]); } }

struct Ring { uint32_t st, ph; };
template<int NST> __device__ __forceinline__ void ring_next(Ring& r) { if (++r.st == NST) { r.st = 0; r.ph ^= 1; } }

struct OpDesc { uint32_t lo, hi, step, step2, nsplit; };

template<int N, int PART> __device__ __forceinline__ void wgmma_ss(float (&d)[N / 2], uint64_t da, uint64_t db, int sc) {
    if constexpr (N == 160) {
        if constexpr (PART == 0) wgmma_ss_n96<0, 1>(*(float(*)[48])&d[0], da, db, sc);
        else wgmma_ss_n64<0, 1>(*(float(*)[32])&d[48], da, db, sc);
    } else if constexpr (N == 192) {
        if constexpr (PART == 0) wgmma_ss_n128<0, 1>(*(float(*)[64])&d[0], da, db, sc);
        else wgmma_ss_n64<0, 1>(*(float(*)[32])&d[64], da, db, sc);
    } else {
        if constexpr (PART == 0) wgmma_ss_n128<0, 1>(*(float(*)[64])&d[0], da, db, sc);
        else wgmma_ss_n96<0, 1>(*(float(*)[48])&d[64], da, db, sc);
    }
}

struct GemmCtx { Ring r; uint32_t sb16, bar_full, bar_empty, peer_off; bool lead; };

template<int N, int NS, int GB>
__device__ __forceinline__ void gemm_loop(float (&acc)[N / 2], int nkb, int first, OpDesc a, OpDesc b, GemmCtx& c) {
    uint32_t prev = 0;
    #pragma unroll 1
    for (int kb = 0; kb < nkb; kb++) {
        mbar_sleep(c.bar_full + 8 * c.r.st, c.r.ph);
        const uint32_t base = c.sb16 + c.r.st * (GST_BYTES / 16);
        const uint64_t da0 = mkdesc(base + a.lo, a.hi), db0 = mkdesc(base + b.lo, b.hi);
        wg_fence();
        #pragma unroll
        for (int k = 0; k < NS; k++) {
            const uint64_t da = da0 + k * a.step, db = db0 + ((k & 1) * b.step + (k >> 1) * b.step2);
            const int sc = (k > 0) | (kb > 0) | !first;
            wgmma_ss<N, 0>(acc, da, db, sc);
            if constexpr (GB > 0) { wg_commit(); wg_wait<GB - 1>(); }
            wgmma_ss<N, 1>(acc, da, db + b.nsplit, sc);
            if constexpr (GB < 0) {
                if ((k + 1) % (-GB) == 0 || k == NS - 1) {
                    wg_commit(); wg_wait<1>();
                    if (k < -GB && kb > 0 && c.lead) release2(c.bar_empty + 8 * prev, c.peer_off);
                }
            }
            if constexpr (GB > 0) {
                wg_commit(); wg_wait<GB - 1>();
                if (k == (GB - 1) / 2 && kb > 0 && c.lead) release2(c.bar_empty + 8 * prev, c.peer_off);
            }
        }
        if constexpr (GB == 0) {
            wg_commit();
            wg_wait<1>();
            if (kb > 0 && c.lead) release2(c.bar_empty + 8 * prev, c.peer_off);
        }
        prev = c.r.st;
        ring_next<GST>(c.r);
    }
    wg_wait<0>();
    if (c.lead) release2(c.bar_empty + 8 * prev, c.peer_off);
    FENCE_F(acc, N / 2);
}

template<int CNT, int SUBS>
__device__ __forceinline__ void retile_ld(uint4 (&v)[CNT], const __nv_bfloat16* src, int pitch, int ncg, int nkg, int cm0, int cnt, int id) {
    const int sub = id >> 3, row = id & 7;
    #pragma unroll
    for (int i = 0; i < CNT; i++) {
        const int l = sub + i * SUBS, cm = cm0 + l, kg = cm / ncg, cg = cm - kg * ncg;
        if (l < cnt && kg < nkg) v[i] = __ldg((const uint4*)(src + (size_t)(kg * 8 + row) * pitch + cg * 8));
    }
}
template<int NG, int CNT, int SUBS, bool PERM>
__device__ __forceinline__ void retile_st(const uint4 (&v)[CNT], int ncg, int nkg, uint8_t* dst, int cm0, int cnt, int id) {
    const int sub = id >> 3, row = id & 7;
    #pragma unroll
    for (int i = 0; i < CNT; i++) {
        const int l = sub + i * SUBS, cm = cm0 + l, kg = cm / ncg, cg = cm - kg * ncg, tile = cg / NG;
        int kd = kg;
        if (PERM) { const int q = kg / 20, rem = kg - q * 20; kd = rem < 4 ? q * 4 + rem : (rem < 12 ? 12 + q * 8 + rem : 36 + q * 8 + rem); }
        if (l < cnt && kg < nkg) *(uint4*)(dst + (size_t)((tile * nkg + kd) * NG + (cg - tile * NG)) * 128 + row * 16) = v[i];
    }
}

__global__ void __cluster_dims__(2, 1, 1) __launch_bounds__(640, 1) mega_kernel(const __grid_constant__ Params p) {
    extern __shared__ uint8_t smem_raw[];
    const uint32_t sb = ((uint32_t)__cvta_generic_to_shared(smem_raw) + 1023u) & ~1023u;
    uint8_t* sm = smem_raw + (sb - (uint32_t)__cvta_generic_to_shared(smem_raw));
    const uint32_t bar_gfull = sb + SM_MISC, bar_gempty = bar_gfull + 64, bar_kfull = bar_gfull + 128, bar_kempty = bar_gfull + 192;
    float* s_gate = (float*)(sm + SM_MISC + 256);
    float* s_stat = (float*)(sm + SM_MISC + 512);
    float* s_red = (float*)(sm + SM_MISC + 768);
    const int ct = (blockIdx.x >> 2) & 3, rb = ((blockIdx.x >> 4) << 2) | (blockIdx.x & 3);
    const int bid = ct * 32 + rb;
    const int rank = rb & 1;
    const int wg = __shfl_sync(0xffffffffu, threadIdx.x >> 7, 0);
    const int tid = threadIdx.x & 127, w = tid >> 5, lane = tid & 31, g = lane >> 2, t = lane & 3;
    uint32_t peer_off;
    asm("mapa.shared::cluster.u32 %0, %1, %2;" : "=r"(peer_off) : "r"(sb), "r"(rank ^ 1));
    peer_off -= sb;

    if (threadIdx.x >= 576 && threadIdx.x < 580) asm volatile("prefetch.tensormap [%0];" :: "l"(&p.mx + (threadIdx.x - 576)) : "memory");
    if (threadIdx.x == 544) {
        l2_prefetch(p.wq + (size_t)bid * 3200, 6400);
        l2_prefetch(p.win + (size_t)bid * 8640, 17280);
    }
    if (__shfl_sync(0xffffffffu, threadIdx.x >> 5, 0) == 16 && elect_one()) {
        for (int i = 0; i < GST; i++) { mbar_init(bar_gfull + 8 * i, 1); mbar_init(bar_gempty + 8 * i, 8); }
        for (int i = 0; i < KST; i++) { mbar_init(bar_kfull + 8 * i, 1); mbar_init(bar_kempty + 8 * i, 24); }
        mbar_init(bar_kfull + 32, 1); mbar_init(bar_kfull + 40, 1); mbar_init(bar_kfull + 48, 1);
        asm volatile("fence.mbarrier_init.release.cluster;" ::: "memory");
        asm volatile("fence.proxy.async.shared::cta;" ::: "memory");
        if (ct == 3) {
            mbar_arrive(bar_gfull + 24);
            mbar_expect(bar_kfull + 48, 2 * 25600 + 1280);
            bulk_ld(sb + SM_W, p.wk, 25600, bar_kfull + 48);
            bulk_ld(sb + SM_W + 25600, p.wv, 25600, bar_kfull + 48);
            bulk_ld(sb + SM_W + 51200, p.gw, 1280, bar_kfull + 48);
            #pragma unroll 1
            for (int kb = 0; kb < 10; kb++) {
                if ((kb & 3) == 0) mbar_expect(bar_gfull + (kb >> 2) * 8, kb < 8 ? 32768 : 16384);
                tma2d(sb + SM_G + (kb >> 2) * GST_BYTES + (kb & 3) * 8192, &p.mx, kb * 64, rb * 64, bar_gfull + (kb >> 2) * 8);
            }
        }
    }
    asm volatile("barrier.cluster.arrive.relaxed;\nbarrier.cluster.wait.acquire;" ::: "memory");

    if (wg == 4) {
        asm volatile("setmaxnreg.dec.sync.aligned.u32 24;");
        const int wu = __shfl_sync(0xffffffffu, w, 0);
        static_assert(GST == 4, "ring indices are derived from a running stage counter");
        #define STG_ADDR(n) (sb + SM_G + ((n) & 3) * GST_BYTES)
        #define STG_FULL(n) (bar_gfull + ((n) & 3) * 8)
        #define STG_WAIT(n) mbar_sleep(bar_gempty + ((n) & 3) * 8, (((n) >> 2) & 1) ^ 1)
        const uint32_t n0 = ct == 3 ? 4 : 0;
        if (wu == 0) {
            uint32_t n = n0;
            if (elect_one()) {
                #pragma unroll 1
                for (int kb = 0; kb < 10; kb++, n++) {
                    STG_WAIT(n);
                    mbar_expect(STG_FULL(n), 8192 + 20480);
                    tma3d_mc(STG_ADDR(n) + 8192 + rank * 10240, &p.mwq, kb * 64 + rank * 32, 5 * ct, STG_FULL(n));
                }
                #pragma unroll 1
                for (int i = 0; i < 20; i++, n++) {
                    STG_WAIT(n);
                    mbar_expect(STG_FULL(n), 8192 + 28672);
                    tma3d_mc(STG_ADDR(n) + 8192 + rank * 14336, &p.mwin, (i < 10 ? i : i - 10) * 64 + rank * 32, (i < 10 ? 27 : 0) + 7 * ct, STG_FULL(n));
                }
            }
            __syncwarp();
            #pragma unroll 1
            for (int it = 0; ; it++) {
                unsigned v;
                asm volatile("ld.acquire.gpu.global.u32 %0, [%1];" : "=r"(v) : "l"(&g_flags[(F_Z2 + lane * 4 + ct) * 8]) : "memory");
                if (__all_sync(0xffffffffu, v != 0)) break;
                if (it > SPIN_LIMIT) SPIN_FAIL(F_Z2);
                __nanosleep(20);
            }
            if (elect_one()) {
                n = n0 + 30;
                fence_async();
                const uint8_t* src = g_z2n + (size_t)ct * 32 * 28672 + rank * 14336;
                #pragma unroll 1
                for (int kb = 0; kb < 32; kb++, n++, src += 28672) {
                    STG_WAIT(n);
                    mbar_expect(STG_FULL(n), 8192 + 28672);
                    bulk_ld_mc(STG_ADDR(n) + 8192 + rank * 14336, src, 14336, STG_FULL(n));
                }
                flag_wait(F_WR, 96);
                fence_async();
                n++;
                #pragma unroll 1
                for (int i = 0; i < 2; i++, n++) {
                    STG_WAIT(n);
                    mbar_expect(STG_FULL(n), 28672);
                    bulk_ld_mc(STG_ADDR(n) + 8192 + rank * 10240, g_wot + (size_t)(ct * 80 + i * 8) * 2560 + rank * 10240, 10240, STG_FULL(n));
                }
                uint32_t k0 = 28 * ct + rank * 4;
                #pragma unroll 1
                for (int i = 0; i < 14; i++, n++) {
                    const uint32_t nk = i == 13 ? 2 : 4;
                    if (i == 13) k0 -= rank * 2;
                    if (k0 >= 108) k0 -= 108;
                    STG_WAIT(n);
                    mbar_expect(STG_FULL(n), nk * 2 * (2560 + 1024));
                    bulk_ld_mc(STG_ADDR(n) + 8192 + rank * nk * 2560, g_woutt + (size_t)(ct * 108 + k0) * 2560, nk * 2560, STG_FULL(n));
                    k0 += 8;
                }
                #pragma unroll 1
                for (int i = 2; i < 10; i++, n++) {
                    STG_WAIT(n);
                    mbar_expect(STG_FULL(n), 28672);
                    bulk_ld_mc(STG_ADDR(n) + 8192 + rank * 10240, g_wot + (size_t)(ct * 80 + i * 8) * 2560 + rank * 10240, 10240, STG_FULL(n));
                }
            }
        } else if (wu == 3) {
            if (elect_one()) {
                uint32_t n = n0;
                #pragma unroll 1
                for (int j = 0; j < 3; j++) {
                    #pragma unroll 1
                    for (int kb = 0; kb < 10; kb++, n++) {
                        STG_WAIT(n);
                        tma2d(STG_ADDR(n), &p.mx, kb * 64, rb * 64, STG_FULL(n));
                    }
                }
                #define STASH_STAGE(which) { STG_WAIT(n); fence_async(); mbar_expect(STG_FULL(n), 28672); \
                    bulk_ld(STG_ADDR(n), g_z1 + (size_t)((which) * NCTA + bid) * 1792, 28672, STG_FULL(n)); n++; }
                #pragma unroll 1
                for (int kb = 0; kb < 32; kb++, n++) {
                    STG_WAIT(n);
                    tma2d(STG_ADDR(n), &p.mwsp, kb * 64, rb * 64, STG_FULL(n));
                }
                STASH_STAGE(0)
                const uint8_t* op = g_op + (size_t)rb * 80 * 1024;
                const uint8_t* hp = g_hp + (size_t)rb * 108 * 1024;
                flag_wait(F_O + rb * 3, 4);
                fence_async();
                #pragma unroll 1
                for (int i = 0; i < 2; i++, n++) { STG_WAIT(n); bulk_ld(STG_ADDR(n), op + i * 8192, 8192, STG_FULL(n)); }
                mbar_sleep(bar_kfull + 40, 0);
                fence_async();
                uint32_t k0 = 28 * ct;
                #pragma unroll 1
                for (int i = 0; i < 14; i++, n++) {
                    if (i == 3) { flag_wait(F_H + rb, 4); fence_async(); }
                    STG_WAIT(n);
                    const uint32_t nb = (i == 13 || k0 == 104) ? 4096 : 8192;
                    bulk_ld(STG_ADDR(n), hp + k0 * 1024, nb, STG_FULL(n));
                    if (k0 == 104 && i != 13) bulk_ld(STG_ADDR(n) + 4096, hp, 4096, STG_FULL(n));
                    k0 += 8; if (k0 >= 108) k0 -= 108;
                }
                #pragma unroll 1
                for (int i = 2; i < 10; i++, n++) {
                    if (i == 2 || i == 6) { flag_wait(F_O + rb * 3 + (i == 2 ? 1 : 2), i == 2 ? 4 : 12); fence_async(); }
                    STG_WAIT(n);
                    bulk_ld(STG_ADDR(n), op + i * 8192, 8192, STG_FULL(n));
                }
            }
            __syncwarp();
            unsigned d = 0;
            if (lane == 0) d = atomicAdd(&g_flags[F_DONE * 8], 1u);
            if (__shfl_sync(0xffffffffu, d, 0) == NCTA - 1) {
                #pragma unroll
                for (int i = 0; i < (F_NUM + 31) / 32; i++) if (i * 32 + lane < F_NUM) g_flags[(i * 32 + lane) * 8] = 0;
            }
        } else if (wu == 1) {
            if (elect_one()) {
                flag_wait(F_KV, 32);
                asm volatile("fence.proxy.async.global;" ::: "memory");
                mbar_expect(bar_kfull + 32, 6144 + 512);
                bulk_ld(sb + SM_KV + 3 * KST_BYTES + 6144, g_kv + 31 * 6144, 6144, bar_kfull + 32);
                bulk_ld(sb + SM_MISC + 512, g_kvmax, 256, bar_kfull + 32);
                bulk_ld(sb + SM_MISC + 256, g_gate + rb * 64, 256, bar_kfull + 32);
                #pragma unroll 1
                for (int i = 0; i < 48; i++) {
                    const uint32_t st = i & 3;
                    if (i >= 3) mbar_sleep(bar_kempty + 8 * st, (((i + 1) >> 2) & 1) ^ 1);
                    mbar_expect(bar_kfull + 8 * st, KST_BYTES);
                    bulk_ld_mc(sb + SM_KV + st * KST_BYTES + rank * 6144, g_kv + (i & 15) * KST_BYTES + rank * 6144, 6144, bar_kfull + 8 * st);
                    if (i == 19 || i == 35) flag_add(F_O + rb * 3 + (i == 35));
                }
            }
        } else {
            if (ct == 3) {
                bar_sync(10, 160);
                if (lane < 2) {
                    const float* r = s_red + 8 + 4 * lane;
                    g_kvmax[lane * 32 + rb] = __uint_as_float(max(max(__float_as_uint(r[0]), __float_as_uint(r[1])), max(__float_as_uint(r[2]), __float_as_uint(r[3]))));
                }
                __syncwarp();
                if (elect_one()) flag_add(F_KV);
                __syncwarp();
            }
            bar_sync(10, 160);
            if (elect_one()) { flag_add(F_H + rb); mbar_arrive(bar_kfull + 40); }
        }
    } else if (wg == 3) {
        asm volatile("setmaxnreg.inc.sync.aligned.u32 144;");
        GemmCtx c{{0, 0}, ((sb + SM_G) & 0x3FFFFu) >> 4, bar_gfull, bar_gempty, peer_off, lane == 0};
        const OpDesc a_sw{0u, 64u | (1u << 30), 2u, 0u, 0u};
        const OpDesc a_t{64u << 16, 8u, 128u, 0u, 0u};
        const OpDesc b_q{512u | (128u << 16), 32u | (2u << 30), 64u, 640u, 384u};
        const OpDesc b_w{512u | (128u << 16), 32u | (2u << 30), 64u, 896u, 512u};
        const OpDesc b_z{512u | (224u << 16), 8u, 448u, 896u, 128u};
        const OpDesc b_o{512u | (160u << 16), 8u, 320u, 640u, 96u};
        const int r0 = 16 * w + g;
        if (ct == 3) {
            float ex[24];
            const uint32_t exlo = (((sb + SM_KV) & 0x3FFFFu) >> 4) | (48u << 16);
            bar_sync(1, 512);
            #pragma unroll 1
            for (int kb = 0; kb < 10; kb++) {
                if ((kb & 3) == 0) mbar_wait(bar_gfull + 8 * (kb >> 2), 0);
                const uint32_t base = c.sb16 + (kb >> 2) * (GST_BYTES / 16) + (kb & 3) * 512;
                wg_fence();
                #pragma unroll
                for (int k = 0; k < 4; k++) wgmma_ss_n48<0, 1>(ex, mkdesc(base + 2 * k, a_sw.hi), mkdesc(exlo + (kb * 4 + k) * 96, 8), (k > 0) | (kb > 0));
                wg_commit();
            }
            wg_wait<0>();
            FENCE_F(ex, 24);
            if (lane < 4) release2(bar_gempty + 8 * lane, peer_off);
            c.r.ph = 1;
            uint8_t* dk = g_kv + ((rb + 31) & 31) * 6144 + 2 * w * 384 + g * 16 + t * 4;
            uint8_t* dv = g_kv + rb * 6144 + 3072 + 2 * w * 384 + g * 16 + t * 4;
            uint32_t mk = 0, mv = 0;
            #pragma unroll
            for (int hi = 0; hi < 2; hi++) {
                const bool alu = (PAT >> (2 * w + hi)) & 1;
                float n2 = 0.f;
                #pragma unroll
                for (int j = 0; j < 3; j++) {
                    uint32_t v = pack_bf16(ex[4 * j + 2 * hi], ex[4 * j + 2 * hi + 1]);
                    const float a = bf_lo(v), b = bf_hi(v);
                    n2 = fmaf(a, a, fmaf(b, b, n2));
                    if (alu) v = pack_bf16(2.f * a, 2.f * b);
                    if (j == 2 && t == 2) v = alu ? 0x3C004446u : 0x3CF14159u;
                    *(uint32_t*)(dk + hi * 384 + j * 128) = v;
                    v = pack_bf16(ex[12 + 4 * j + 2 * hi], ex[12 + 4 * j + 2 * hi + 1]);
                    if (j < 2 || t < 2) mv = max(mv, max((v << 16) & 0x7FFF0000u, v & 0x7FFF0000u));
                    if (j == 2 && t == 3) {
                        g_gate[rb * 64 + r0 + 8 * hi] = 1.f / (1.f + __expf(-ex[20 + 2 * hi]));
                        v = 0u;
                    }
                    if (j == 2 && t == 2) v = 0x00003F80u;
                    *(uint32_t*)(dv + hi * 384 + j * 128) = v;
                }
                n2 += __shfl_xor_sync(0xffffffffu, n2, 1); n2 += __shfl_xor_sync(0xffffffffu, n2, 2);
                mk = max(mk, __float_as_uint(n2) & 0x7FFFFFFFu);
            }
            mk = __reduce_max_sync(0xffffffffu, mk); mv = __reduce_max_sync(0xffffffffu, mv);
            if (lane == 0) { s_red[8 + w] = __uint_as_float(mk); s_red[12 + w] = __uint_as_float(mv); }
            bar_arrive(10, 160);
        }
        {
            float acc[80];
            gemm_loop<160, 4, 0>(acc, 10, 1, a_sw, b_q, c);
            uint8_t* qs = sm + SM_Q + 2 * w * 128 + g * 16;
            #pragma unroll
            for (int j = 0; j < 20; j++) {
                const int h0 = (8 * j) / 20, d0 = (8 * j) % 20, d = d0 + 2 * t;
                const int off = d < 20 ? h0 * 3072 + (d >> 3) * 1024 + (d & 7) * 2 : (h0 + 1) * 3072 + (d - 20) * 2;
                *(uint32_t*)(qs + off) = pack_bf16(acc[4 * j] * 0.3225964182229561f, acc[4 * j + 1] * 0.3225964182229561f);
                *(uint32_t*)(qs + off + 128) = pack_bf16(acc[4 * j + 2] * 0.3225964182229561f, acc[4 * j + 3] * 0.3225964182229561f);
            }
            asm volatile("fence.proxy.async.shared::cta;" ::: "memory");
            bar_arrive(2, 384);
            bar_arrive(13, 256);
        }
        {
            float acc[112];
            #pragma unroll
            for (int i = 96; i < 112; i++) acc[i] = 0.f;
            #define GEMM_Z(GBX, nkb, first, bd) { if (ct == 3) gemm_loop<192, 4, GBX>(*(float(*)[96])&acc[0], nkb, first, a_sw, bd, c); \
                                                  else gemm_loop<224, 4, GBX>(acc, nkb, first, a_sw, bd, c); }
            GEMM_Z(GB2, 10, 1, b_w)
            uint4* z1p = g_z1 + (size_t)bid * 14 * 128 + tid;
            {
                float s0 = 0.f, q0 = 0.f, s1 = 0.f, q1 = 0.f;
                #pragma unroll
                for (int j = 0; j < 14; j++) {
                    float y[8];
                    #pragma unroll
                    for (int i = 0; i < 8; i++) y[i] = gelu2_tanh(acc[8 * j + i]);
                    s0 += (y[0] + y[1]) + (y[4] + y[5]); q0 = fmaf(y[0], y[0], fmaf(y[1], y[1], fmaf(y[4], y[4], fmaf(y[5], y[5], q0))));
                    s1 += (y[2] + y[3]) + (y[6] + y[7]); q1 = fmaf(y[2], y[2], fmaf(y[3], y[3], fmaf(y[6], y[6], fmaf(y[7], y[7], q1))));
                    z1p[(NCTA * 14 + j) * 128] = make_uint4(pack_bf16(y[0], y[1]), pack_bf16(y[2], y[3]), pack_bf16(y[4], y[5]), pack_bf16(y[6], y[7]));
                }
                #pragma unroll
                for (int o = 1; o <= 2; o <<= 1) {
                    s0 += __shfl_xor_sync(0xffffffffu, s0, o); q0 += __shfl_xor_sync(0xffffffffu, q0, o);
                    s1 += __shfl_xor_sync(0xffffffffu, s1, o); q1 += __shfl_xor_sync(0xffffffffu, q1, o);
                }
                if (t < 2) asm volatile("st.relaxed.gpu.global.b64 [%0], %1;" :: "l"(&g_part[(rb * 4 + ct) * 64 + r0 + 8 * t]),
                                        "l"(mkdesc(__float_as_uint(t ? s1 : s0), __float_as_uint(t ? q1 : q0) | 0x80000000u)) : "memory");
            }
            bar_arrive(11, 256);
            GEMM_Z(GB3, 10, 1, b_w)
            #pragma unroll
            for (int j = 0; j < 14; j++)
                z1p[j * 128] = make_uint4(pack_bf16(gelu2_tanh(acc[8 * j]), gelu2_tanh(acc[8 * j + 1])), pack_bf16(gelu2_tanh(acc[8 * j + 2]), gelu2_tanh(acc[8 * j + 3])),
                                          pack_bf16(gelu2_tanh(acc[8 * j + 4]), gelu2_tanh(acc[8 * j + 5])), pack_bf16(gelu2_tanh(acc[8 * j + 6]), gelu2_tanh(acc[8 * j + 7])));
            const float b0 = __bfloat162float(p.bsp[rb * 64 + r0]), b1 = __bfloat162float(p.bsp[rb * 64 + r0 + 8]);
            GEMM_Z(GB4, 32, 1, b_z)
            bar_sync(8, 512);
            const float g0 = 0.5f - 0.5f * s_gate[r0], g1 = 0.5f - 0.5f * s_gate[r0 + 8];
            {
                mbar_wait(c.bar_full + 8 * c.r.st, c.r.ph);
                const uint4* zs = (const uint4*)(sm + SM_G + c.r.st * GST_BYTES) + tid;
                uint8_t* dst = g_hp + (size_t)((rb * 108 + 28 * ct) * 8 + 2 * w) * 128 + g * 16 + t * 4;
                const float e0 = b0 * g0, e1 = b1 * g1;
                #pragma unroll
                for (int j = 0; j < 14; j++) {
                    if (j < 12 || ct < 3) {
                        const uint4 v = zs[j * 128];
                        *(uint32_t*)(dst + (2 * j) * 1024) = pack_bf16(fmaf(acc[8 * j], g0, e0) * bf_lo(v.x), fmaf(acc[8 * j + 1], g0, e0) * bf_hi(v.x));
                        *(uint32_t*)(dst + (2 * j) * 1024 + 128) = pack_bf16(fmaf(acc[8 * j + 2], g1, e1) * bf_lo(v.y), fmaf(acc[8 * j + 3], g1, e1) * bf_hi(v.y));
                        *(uint32_t*)(dst + (2 * j + 1) * 1024) = pack_bf16(fmaf(acc[8 * j + 4], g0, e0) * bf_lo(v.z), fmaf(acc[8 * j + 5], g0, e0) * bf_hi(v.z));
                        *(uint32_t*)(dst + (2 * j + 1) * 1024 + 128) = pack_bf16(fmaf(acc[8 * j + 6], g1, e1) * bf_lo(v.w), fmaf(acc[8 * j + 7], g1, e1) * bf_hi(v.w));
                    }
                }
                __syncwarp();
                if (c.lead) release2(c.bar_empty + 8 * c.r.st, c.peer_off);
                ring_next<GST>(c.r);
            }
            bar_arrive(10, 160);
        }
        {
            float acc[80];
            gemm_loop<160, 4, GB5>(acc, 15, 1, a_t, b_o, c);
            gemm_loop<160, 2, GB5>(acc, 1, 0, a_t, b_o, c);
            gemm_loop<160, 4, GB5>(acc, 4, 0, a_t, b_o, c);
            if (tid < 64) g_part[(rb * 4 + ct) * 64 + tid] = 0ull;
            gemm_loop<160, 4, 0>(acc, 4, 0, a_t, b_o, c);
            uint32_t* os = (uint32_t*)(sm + SM_Q) + r0 * (QS_PITCH / 2) + t;
            #pragma unroll
            for (int j = 0; j < 20; j++) {
                os[4 * j] = pack_bf16(acc[4 * j], acc[4 * j + 1]);
                os[8 * (QS_PITCH / 2) + 4 * j] = pack_bf16(acc[4 * j + 2], acc[4 * j + 3]);
            }
            asm volatile("fence.proxy.async.shared::cta;" ::: "memory");
            __syncwarp();
            if (lane < 16) {
                const int row = 16 * w + lane;
                asm volatile("cp.async.bulk.global.shared::cta.bulk_group [%0], [%1], 320;"
                             :: "l"(p.out + (size_t)(rb * 64 + row) * DM + 160 * ct), "r"(sb + SM_Q + row * (QS_PITCH * 2)) : "memory");
                asm volatile("cp.async.bulk.commit_group;\ncp.async.bulk.wait_group.read 0;" ::: "memory");
            }
            __syncwarp();
            asm volatile("barrier.cluster.arrive.relaxed;\nbarrier.cluster.wait;" ::: "memory");
        }
    } else {
        asm volatile("setmaxnreg.inc.sync.aligned.u32 104;");
        const int atid = threadIdx.x;
        {
            *(uint2*)(sm + SM_Q + 8 * 3072 + (atid & 127) * 8) = make_uint2(0u, 0u);
            if (ct < 3) {
                uint4 w1[2], w2[2];
                const int c1 = bid * 67, c2 = bid * 90;
                retile_ld<2, 48>(w1, p.wo, DM, 80, 80, c1, 67, atid);
                retile_ld<2, 48>(w2, p.wout, DM, 80, 108, c2, 90, atid);
                retile_st<20, 2, 48, true>(w1, 80, 80, g_wot, c1, 67, atid);
                retile_st<20, 2, 48, false>(w2, 80, 108, g_woutt, c2, 90, atid);
                bar_sync(9, 384);
                if (atid == 256) flag_add(F_WR);
            } else {
                mbar_wait(bar_kfull + 48, 0);
                #pragma unroll 2
                for (int e = atid; e < 1280; e += 384) {
                    const int m = e >= 640, k = e - m * 640;
                    const uint2* src = (const uint2*)(sm + SM_W + e * 40);
                    const uint2 a = src[0], b = src[1], c = src[2], d = src[3], f = src[4];
                    const uint32_t gt = m ? *(const unsigned short*)(sm + SM_W + 51200 + k * 2) : 0u;
                    uint4* dst = (uint4*)(sm + SM_KV + (k >> 3) * 768 + (k & 7) * 16 + m * 384);
                    dst[0] = make_uint4(a.x, a.y, b.x, b.y); dst[8] = make_uint4(c.x, c.y, d.x, d.y); dst[16] = make_uint4(f.x, f.y, 0u, gt);
                }
                asm volatile("fence.proxy.async.shared::cta;" ::: "memory");
                bar_arrive(1, 512);
            }
        }
        const uint32_t half2c = *(const volatile uint32_t*)&g_const[0];
        if (wg == 2) {
            const int r0 = 16 * w + g;
            uint4* z1p = g_z1 + (size_t)bid * 14 * 128 + tid;
            uint4 v[14];
            bar_sync(11, 256);
            #pragma unroll
            for (int j = 0; j < 14; j++) v[j] = __ldcg(z1p + (NCTA * 14 + j) * 128);
            float s0, q0, s1, q1;
            {
                unsigned long long a, b;
                const unsigned long long* pa_ = &g_part[(rb * 4 + t) * 64 + r0];
                #pragma unroll 1
                for (int it = 0; ; it++) {
                    asm volatile("ld.relaxed.gpu.global.b64 %0, [%1];" : "=l"(a) : "l"(pa_) : "memory");
                    asm volatile("ld.relaxed.gpu.global.b64 %0, [%1];" : "=l"(b) : "l"(pa_ + 8) : "memory");
                    if (__all_sync(0xffffffffu, ((a & b) >> 63) != 0)) break;
                    if (it > SPIN_LIMIT) SPIN_FAIL(0x7000);
                    __nanosleep(100);
                }
                s0 = __uint_as_float((uint32_t)a); q0 = __uint_as_float((uint32_t)(a >> 32) & 0x7FFFFFFFu);
                s1 = __uint_as_float((uint32_t)b); q1 = __uint_as_float((uint32_t)(b >> 32) & 0x7FFFFFFFu);
                #pragma unroll
                for (int o = 1; o <= 2; o <<= 1) {
                    s0 += __shfl_xor_sync(0xffffffffu, s0, o); q0 += __shfl_xor_sync(0xffffffffu, q0, o);
                    s1 += __shfl_xor_sync(0xffffffffu, s1, o); q1 += __shfl_xor_sync(0xffffffffu, q1, o);
                }
            }
            const float m0 = s0 * (1.f / FH), m1 = s1 * (1.f / FH);
            const float rs0 = rsqrtf(fmaxf(q0 * (1.f / FH) - m0 * m0, 0.f) + 4e-5f), rs1 = rsqrtf(fmaxf(q1 * (1.f / FH) - m1 * m1, 0.f) + 4e-5f);
            const float c0 = -m0 * rs0, c1 = -m1 * rs1;
            uint8_t* dst = g_z2n + (size_t)(ct * 32 + rb) * 28672 + (2 * w) * 3584 + g * 16 + t * 4;
            #pragma unroll
            for (int j = 0; j < 14; j++) {
                *(uint32_t*)(dst + 2 * j * 128) = pack_bf16(fmaf(bf_lo(v[j].x), rs0, c0), fmaf(bf_hi(v[j].x), rs0, c0));
                *(uint32_t*)(dst + 3584 + 2 * j * 128) = pack_bf16(fmaf(bf_lo(v[j].y), rs1, c1), fmaf(bf_hi(v[j].y), rs1, c1));
                *(uint32_t*)(dst + (2 * j + 1) * 128) = pack_bf16(fmaf(bf_lo(v[j].z), rs0, c0), fmaf(bf_hi(v[j].z), rs0, c0));
                *(uint32_t*)(dst + 3584 + (2 * j + 1) * 128) = pack_bf16(fmaf(bf_lo(v[j].w), rs1, c1), fmaf(bf_hi(v[j].w), rs1, c1));
            }
            bar_sync(6, 128);
            if (tid == 0) flag_add(F_Z2 + rb * 4 + ct);
        }
        if (wg == 2) bar_sync(13, 256); else bar_sync(2, 384);
        const int p0 = wg == 2 ? 1 : 0;
        #define HEAD(ps) ((ps) == 0 ? wg : 3 * (ps) - 1 + wg)
        uint32_t qmax2 = 0;
        #pragma unroll 1
        for (int i = p0 + (tid >> 6); i < 3; i += 2) {
            uint8_t* qrow = sm + SM_Q + HEAD(i) * 3072 + (tid & 63) * 16;
            const uint4 a = *(const uint4*)qrow, b = *(const uint4*)(qrow + 1024);
            const uint2 c = *(const uint2*)(qrow + 2048);
            #define SQ(v) (bf_lo(v) * bf_lo(v) + bf_hi(v) * bf_hi(v))
            const float n = SQ(a.x) + SQ(a.y) + SQ(a.z) + SQ(a.w) + SQ(b.x) + SQ(b.y) + SQ(b.z) + SQ(b.w) + SQ(c.x) + SQ(c.y);
            qmax2 = max(qmax2, __float_as_uint(n) & 0x7FFFFFFFu);
            *(uint2*)(qrow + 2048 + 8) = make_uint2(0x3F803F80u, 0u);
        }
        asm volatile("fence.proxy.async.shared::cta;" ::: "memory");
        mbar_sleep(bar_kfull + 32, 0);
        bar_arrive(8, 512);
        uint32_t safe;
        {
            const float kmax2 = __uint_as_float(__reduce_max_sync(0xffffffffu, __float_as_uint(s_stat[lane])));
            const int ev = (int)(__reduce_max_sync(0xffffffffu, __float_as_uint(s_stat[32 + lane])) >> 23) - 126;
            const float bmax = (float)min(102 - max(ev, 1), 100 + ev);
            const bool ok = bmax > 0.f && __uint_as_float(qmax2) * kmax2 <= bmax * bmax;
            asm volatile("{\n.reg .pred p, q;\nsetp.ne.u32 p, %1, 0;\nbarrier.red.and.pred.aligned q, %2, 128, p;\nselp.u32 %0, 1, 0, q;\n}"
                         : "=r"(safe) : "r"((uint32_t)ok), "r"(4 + wg) : "memory");
            safe = __shfl_sync(0xffffffffu, safe, 0);
            if (!safe) {
                #pragma unroll 1
                for (int i = p0 + (tid >> 6); i < 3; i += 2) *(uint2*)(sm + SM_Q + HEAD(i) * 3072 + (tid & 63) * 16 + 2048 + 8) = make_uint2(0u, 0u);
                asm volatile("fence.proxy.async.shared::cta;" ::: "memory");
                bar_sync(4 + wg, 128);
            }
        }
        const uint32_t kv16 = ((sb + SM_KV) & 0x3FFFFu) >> 4;
        constexpr uint32_t KLBO = 8u << 16, KHI = 24u, VLBO = (24u << 16) + 192u, VHI = 8u;
        const bool lead = lane == 0;
        const int r0 = 16 * w + g;
        static_assert(KST == 4, "ring phases below assume 4 stages");
        if (wg == 2) {
            bar_sync(14, 256);
            mbar_wait(bar_kfull + 24, 1);
        }
        const uint32_t q16 = ((sb + SM_Q) & 0x3FFFFu) >> 4;
        uint64_t qa = mkdesc(q16 + HEAD(p0) * 192 + (64u << 16), 8), qb = mkdesc(q16 + HEAD(p0) * 192 + 128 + ((uint32_t)(1536 - 128 - HEAD(p0) * 192) << 16), 8);
        #define NEXT_HEAD(ps) { const uint32_t d_ = (ps) == 0 ? 384 : 576; qa += d_; qb += (uint64_t)d_ - ((uint64_t)d_ << 16); }
        const uint64_t dk = mkdesc(kv16 + KLBO, KHI), dv = mkdesc(kv16 + VLBO, VHI);
        const uint32_t kep = bar_kempty + peer_off;
        uint32_t rc = lead ? (wg == 0 ? 2 : 1) : 0;
        float o[12];
        #pragma unroll
        for (int i = 0; i < 12; i++) o[i] = 0.f;
        float s[32]; uint32_t pa[16], pb[16];
        FENCE_F(o, 12);
        #define QK(off) wgmma_ss_n64<0, 0>(s, qa, dk + (off), 0); wgmma_ss_n64<0, 0>(s, qb, dk + (off) + 16, 1);
        #define PV(pp, off) wgmma_rs_n24<1>(o, pp[0], pp[1], pp[2], pp[3], dv + (off), 1); wgmma_rs_n24<1>(o, pp[4], pp[5], pp[6], pp[7], dv + (off) + 48, 1); \
                            wgmma_rs_n24<1>(o, pp[8], pp[9], pp[10], pp[11], dv + (off) + 96, 1); wgmma_rs_n24<1>(o, pp[12], pp[13], pp[14], pp[15], dv + (off) + 144, 1);
        #define STORE_O(h) { \
            const float l0 = __shfl_sync(0xffffffffu, o[8], (lane & ~3) | 2), l1 = __shfl_sync(0xffffffffu, o[10], (lane & ~3) | 2); \
            const float i0 = __fdividef(s_gate[r0], l0), i1 = __fdividef(s_gate[r0 + 8], l1);        \
            _Pragma("unroll") for (int b = 0; b < 3; b++) { \
                if (b < 2 || t < 2) { \
                    const int cq = 20 * (h) + 8 * b + 2 * t, col = cq < 32 ? ct * 32 + cq : (cq < 96 ? 96 + ct * 64 + cq : 288 + ct * 64 + cq); \
                    uint8_t* dst = g_op + (size_t)((rb * 80 + (col >> 3)) * 8 + 2 * w) * 128 + g * 16 + (col & 7) * 2; \
                    *(uint32_t*)dst = pack_bf16(o[4 * b] * i0, o[4 * b + 1] * i0); \
                    *(uint32_t*)(dst + 128) = pack_bf16(o[4 * b + 2] * i1, o[4 * b + 3] * i1); \
                } \
            } \
            _Pragma("unroll") for (int i = 0; i < 12; i++) o[i] = 0.f; \
            FENCE_F(o, 12); \
 \
            __syncwarp(); }
        if (safe) {
            wg_fence();
            QK(3 * 768 + 384)
            wg_commit();
            wg_wait<0>();
            FENCE_F(s, 32);
            release2n(bar_kempty + 24, kep + 24, rc);
            EXPBLK(pa, s);
            FENCE_R(pa, 16);
            #define HALF(off, pin, pout) \
                wg_fence(); \
                QK(off) \
                wg_commit(); \
                PV(pin, off) \
                wg_commit(); \
                wg_wait<1>(); \
                FENCE_F(s, 32); \
                EXPBLK(pout, s); \
                FENCE_R(pout, 16); \
                wg_wait<0>();
            #pragma unroll 1
            for (int J4 = 4 * p0; J4 < 12; J4++) {
                const uint32_t ph = J4 & 1;
                #pragma unroll
                for (int st = 0; st < 4; st++) {
                    mbar_wait(bar_kfull + 8 * st, ph);
                    if (st == 3 && J4 == 3 && wg == 0) bar_arrive(14, 256);
                    HALF(st * 768, pa, pb)
                    if (st == 3 && (J4 & 3) == 3 && J4 < 11) NEXT_HEAD(J4 >> 2)
                    HALF(st * 768 + 384, pb, pa)
                    if (st < 3) release2n(bar_kempty + 8 * st, kep + 8 * st, rc);
                }
                if ((J4 & 3) == 3) {
                    FENCE_F(o, 12);
                    STORE_O(HEAD(J4 >> 2))
                    rc = lead ? 1 : 0;
                }
                release2n(bar_kempty + 24, kep + 24, rc);
            }
        } else {
            float m0 = -INFINITY, m1 = -INFINITY;
            #pragma unroll 1
            for (int u = 32 * p0; u < 96; u++) {
                const int J = u >> 1;
                if ((u & 1) == 0) mbar_wait(bar_kfull + 8 * (J & 3), (J >> 2) & 1);
                if (u == 30 && wg == 0) bar_arrive(14, 256);
                wg_fence();
                QK(((u + 7) & 7) * 384)
                wg_commit();
                wg_wait<0>();
                FENCE_F(s, 32);
                float x0 = m0, x1 = m1;
                #pragma unroll
                for (int b = 0; b < 8; b++) {
                    const float f = ((PAT >> b) & 1) ? 0.5f : 1.f;
                    s[4 * b] *= f; s[4 * b + 1] *= f; s[4 * b + 2] *= f; s[4 * b + 3] *= f;
                    x0 = fmaxf(x0, fmaxf(s[4 * b], s[4 * b + 1])); x1 = fmaxf(x1, fmaxf(s[4 * b + 2], s[4 * b + 3]));
                }
                x0 = fmaxf(x0, __shfl_xor_sync(0xffffffffu, x0, 1)); x0 = fmaxf(x0, __shfl_xor_sync(0xffffffffu, x0, 2));
                x1 = fmaxf(x1, __shfl_xor_sync(0xffffffffu, x1, 1)); x1 = fmaxf(x1, __shfl_xor_sync(0xffffffffu, x1, 2));
                const float f0 = exp2f(m0 - x0), f1 = exp2f(m1 - x1);
                m0 = x0; m1 = x1;
                #pragma unroll
                for (int b = 0; b < 3; b++) { o[4 * b] *= f0; o[4 * b + 1] *= f0; o[4 * b + 2] *= f1; o[4 * b + 3] *= f1; }
                #pragma unroll
                for (int b = 0; b < 8; b++) {
                    pa[2 * b] = exp2_mufu(s[4 * b] - m0, s[4 * b + 1] - m0);
                    pa[2 * b + 1] = exp2_mufu(s[4 * b + 2] - m1, s[4 * b + 3] - m1);
                }
                FENCE_R(pa, 16); FENCE_F(o, 12);
                wg_fence();
                PV(pa, (u & 7) * 384)
                wg_commit();
                wg_wait<0>();
                FENCE_F(o, 12);
                if ((u & 1) == 0) release2n(bar_kempty + 8 * ((J + 3) & 3), kep + 8 * ((J + 3) & 3), rc);
                if ((u & 31) == 31) {
                    STORE_O(HEAD(u >> 5))
                    m0 = -INFINITY; m1 = -INFINITY;
                    NEXT_HEAD(u >> 5)
                    rc = lead ? 1 : 0;
                }
            }
        }
        bar_sync(4 + wg, 128);
        if (tid == 0) flag_add(F_O + rb * 3 + 2);
    }
}

typedef CUresult (*EncodeFn)(CUtensorMap*, CUtensorMapDataType, cuuint32_t, void*, const cuuint64_t*, const cuuint64_t*, const cuuint32_t*,
                             const cuuint32_t*, CUtensorMapInterleave, CUtensorMapSwizzle, CUtensorMapL2promotion, CUtensorMapFloatOOBfill);

void make_map(EncodeFn fn, CUtensorMap* m, const void* ptr, uint64_t cols, uint64_t rows, uint32_t bc, uint32_t br, CUtensorMapSwizzle sw) {
    cuuint64_t dims[2] = {cols, rows}, strides[1] = {cols * 2};
    cuuint32_t box[2] = {bc, br}, es[2] = {1, 1};
    fn(m, CU_TENSOR_MAP_DATA_TYPE_BFLOAT16, 2, const_cast<void*>(ptr), dims, strides, box, es, CU_TENSOR_MAP_INTERLEAVE_NONE, sw,
       CU_TENSOR_MAP_L2_PROMOTION_L2_128B, CU_TENSOR_MAP_FLOAT_OOB_FILL_NONE);
}

void make_map3(EncodeFn fn, CUtensorMap* m, const void* ptr, uint64_t cols, uint64_t rows, uint32_t natoms) {
    cuuint64_t dims[3] = {32, rows, cols / 32}, strides[2] = {cols * 2, 64};
    cuuint32_t box[3] = {32, 32, natoms}, es[3] = {1, 1, 1};
    fn(m, CU_TENSOR_MAP_DATA_TYPE_BFLOAT16, 3, const_cast<void*>(ptr), dims, strides, box, es, CU_TENSOR_MAP_INTERLEAVE_NONE, CU_TENSOR_MAP_SWIZZLE_64B,
       CU_TENSOR_MAP_L2_PROMOTION_L2_128B, CU_TENSOR_MAP_FLOAT_OOB_FILL_NONE);
}

}

extern "C" void kernel_launch(void* const* d_in, const int* in_sizes, int n_in, void* d_out, int out_size) {
    static EncodeFn fn = nullptr;
    if (!fn) {
        cudaDriverEntryPointQueryResult qr;
        void* f = nullptr;
        cudaGetDriverEntryPoint("cuTensorMapEncodeTiled", &f, cudaEnableDefault, &qr);
        fn = (EncodeFn)f;
        cudaFuncSetAttribute(mega_kernel, cudaFuncAttributeMaxDynamicSharedMemorySize, SM_TOTAL);
    }
    Params p;
    const __nv_bfloat16* x = (const __nv_bfloat16*)d_in[0];
    make_map(fn, &p.mx, x, DM, S_LEN, 64, 64, CU_TENSOR_MAP_SWIZZLE_128B);
    make_map(fn, &p.mwsp, d_in[7], S_LEN, S_LEN, 64, 64, CU_TENSOR_MAP_SWIZZLE_128B);
    make_map3(fn, &p.mwq, d_in[1], DM, DM, 5);
    make_map3(fn, &p.mwin, d_in[6], 2 * FH, DM, 7);
    p.wq = (const __nv_bfloat16*)d_in[1];
    p.win = (const __nv_bfloat16*)d_in[6];
    p.wk = (const __nv_bfloat16*)d_in[2];
    p.wv = (const __nv_bfloat16*)d_in[3];
    p.bsp = (const __nv_bfloat16*)d_in[8];
    p.gw = (const __nv_bfloat16*)d_in[10];
    p.wo = (const __nv_bfloat16*)d_in[4];
    p.wout = (const __nv_bfloat16*)d_in[9];
    p.out = (__nv_bfloat16*)d_out;
    mega_kernel<<<NCTA, 640, SM_TOTAL>>>(p);
}
```

```cpp
#include <cuda_runtime.h>
#include <cuda_bf16.h>
#include <cuda.h>
#include <stdint.h>

namespace {

constexpr int S_LEN = 2048, DM = 640, FH = 864;
constexpr int NCTA = 128;
#define PAT8 0xB7u
constexpr uint32_t PAT = PAT8 * 0x101u;
#define GB2 -2
#define GB3 -2
#define GB4 -1
#define GB5 -1
constexpr int GST = 4;
constexpr int GST_BYTES = 36864;
constexpr int KST = 4;
constexpr int KST_BYTES = 12288;
constexpr int QS_PITCH = 168;
constexpr int SM_G = 0;
constexpr int SM_KV = SM_G + GST * GST_BYTES;
constexpr int SM_Q = SM_KV + KST * KST_BYTES;
constexpr int SM_MISC = SM_Q + 8 * 3072 + 1024;
constexpr int SM_W = SM_G + 2 * GST_BYTES + 16384;
constexpr int SM_TOTAL = SM_MISC + 2048 + 1024;

constexpr int F_KV = 0, F_DONE = 1, F_WR = 2, F_Z2 = 3, F_H = F_Z2 + 128, F_O = F_H + 32, F_NUM = F_O + 96;

__device__ __align__(1024) uint8_t g_kv[16 * KST_BYTES];
__device__ __align__(1024) uint8_t g_z2n[4 * 32 * 28672];
__device__ __align__(1024) uint8_t g_hp[32 * 108 * 1024];
__device__ __align__(1024) uint8_t g_op[32 * 80 * 1024];
__device__ __align__(1024) uint8_t g_wot[4 * 80 * 2560];
__device__ __align__(1024) uint8_t g_woutt[4 * 108 * 2560];
__device__ __align__(1024) uint4 g_z1[2 * NCTA * 14 * 128];
__device__ unsigned long long g_part[32 * 4 * 64];
__device__ __align__(128) float g_kvmax[64];
__device__ __align__(128) float g_gate[S_LEN];
__device__ unsigned g_flags[F_NUM * 8];
__device__ uint32_t g_const[1] = {0x3F013F01u};

struct Params {
    CUtensorMap mx, mwsp, mwq, mwin;
    const __nv_bfloat16 *wk, *wv, *bsp, *gw, *wo, *wout, *wq, *win;
    __nv_bfloat16* out;
};

template<int TB> __device__ __forceinline__ void wgmma_rs_n24(float (&d)[12], uint32_t a0, uint32_t a1, uint32_t a2, uint32_t a3, uint64_t db, int scale_d) {
  asm volatile("{\n.reg .pred p;\nsetp.ne.b32 p, %17, 0;\nwgmma.mma_async.sync.aligned.m64n24k16.f32.bf16.bf16 {%0,%1,%2,%3,%4,%5,%6,%7,%8,%9,%10,%11}, {%12,%13,%14,%15}, %16, p, 1, 1, %18;\n}"
    : "+f"(d[0]), "+f"(d[1]), "+f"(d[2]), "+f"(d[3]), "+f"(d[4]), "+f"(d[5]), "+f"(d[6]), "+f"(d[7]), "+f"(d[8]), "+f"(d[9]), "+f"(d[10]), "+f"(d[11])
    : "r"(a0), "r"(a1), "r"(a2), "r"(a3), "l"(db), "r"(scale_d), "n"(TB));
}
template<int TA, int TB> __device__ __forceinline__ void wgmma_ss_n48(float (&d)[24], uint64_t da, uint64_t db, int scale_d) {
  asm volatile("{\n.reg .pred p;\nsetp.ne.b32 p, %26, 0;\nwgmma.mma_async.sync.aligned.m64n48k16.f32.bf16.bf16 {%0,%1,%2,%3,%4,%5,%6,%7,%8,%9,%10,%11,%12,%13,%14,%15,%16,%17,%18,%19,%20,%21,%22,%23}, %24, %25, p, 1, 1, %27, %28;\n}"
    : "+f"(d[0]), "+f"(d[1]), "+f"(d[2]), "+f"(d[3]), "+f"(d[4]), "+f"(d[5]), "+f"(d[6]), "+f"(d[7]), "+f"(d[8]), "+f"(d[9]), "+f"(d[10]), "+f"(d[11]), "+f"(d[12]), "+f"(d[13]), "+f"(d[14]), "+f"(d[15]), "+f"(d[16]), "+f"(d[17]), "+f"(d[18]), "+f"(d[19]), "+f"(d[20]), "+f"(d[21]), "+f"(d[22]), "+f"(d[23])
    : "l"(da), "l"(db), "r"(scale_d), "n"(TA), "n"(TB));
}
template<int TA, int TB> __device__ __forceinline__ void wgmma_ss_n64(float (&d)[32], uint64_t da, uint64_t db, int scale_d) {
  asm volatile("{\n.reg .pred p;\nsetp.ne.b32 p, %34, 0;\nwgmma.mma_async.sync.aligned.m64n64k16.f32.bf16.bf16 {%0,%1,%2,%3,%4,%5,%6,%7,%8,%9,%10,%11,%12,%13,%14,%15,%16,%17,%18,%19,%20,%21,%22,%23,%24,%25,%26,%27,%28,%29,%30,%31}, %32, %33, p, 1, 1, %35, %36;\n}"
    : "+f"(d[0]), "+f"(d[1]), "+f"(d[2]), "+f"(d[3]), "+f"(d[4]), "+f"(d[5]), "+f"(d[6]), "+f"(d[7]), "+f"(d[8]), "+f"(d[9]), "+f"(d[10]), "+f"(d[11]), "+f"(d[12]), "+f"(d[13]), "+f"(d[14]), "+f"(d[15]), "+f"(d[16]), "+f"(d[17]), "+f"(d[18]), "+f"(d[19]), "+f"(d[20]), "+f"(d[21]), "+f"(d[22]), "+f"(d[23]), "+f"(d[24]), "+f"(d[25]), "+f"(d[26]), "+f"(d[27]), "+f"(d[28]), "+f"(d[29]), "+f"(d[30]), "+f"(d[31])
    : "l"(da), "l"(db), "r"(scale_d), "n"(TA), "n"(TB));
}
template<int TA, int TB> __device__ __forceinline__ void wgmma_ss_n96(float (&d)[48], uint64_t da, uint64_t db, int scale_d) {
  asm volatile("{\n.reg .pred p;\nsetp.ne.b32 p, %50, 0;\nwgmma.mma_async.sync.aligned.m64n96k16.f32.bf16.bf16 {%0,%1,%2,%3,%4,%5,%6,%7,%8,%9,%10,%11,%12,%13,%14,%15,%16,%17,%18,%19,%20,%21,%22,%23,%24,%25,%26,%27,%28,%29,%30,%31,%32,%33,%34,%35,%36,%37,%38,%39,%40,%41,%42,%43,%44,%45,%46,%47}, %48, %49, p, 1, 1, %51, %52;\n}"
    : "+f"(d[0]), "+f"(d[1]), "+f"(d[2]), "+f"(d[3]), "+f"(d[4]), "+f"(d[5]), "+f"(d[6]), "+f"(d[7]), "+f"(d[8]), "+f"(d[9]), "+f"(d[10]), "+f"(d[11]), "+f"(d[12]), "+f"(d[13]), "+f"(d[14]), "+f"(d[15]), "+f"(d[16]), "+f"(d[17]), "+f"(d[18]), "+f"(d[19]), "+f"(d[20]), "+f"(d[21]), "+f"(d[22]), "+f"(d[23]), "+f"(d[24]), "+f"(d[25]), "+f"(d[26]), "+f"(d[27]), "+f"(d[28]), "+f"(d[29]), "+f"(d[30]), "+f"(d[31]), "+f"(d[32]), "+f"(d[33]), "+f"(d[34]), "+f"(d[35]), "+f"(d[36]), "+f"(d[37]), "+f"(d[38]), "+f"(d[39]), "+f"(d[40]), "+f"(d[41]), "+f"(d[42]), "+f"(d[43]), "+f"(d[44]), "+f"(d[45]), "+f"(d[46]), "+f"(d[47])
    : "l"(da), "l"(db), "r"(scale_d), "n"(TA), "n"(TB));
}
template<int TA, int TB> __device__ __forceinline__ void wgmma_ss_n128(float (&d)[64], uint64_t da, uint64_t db, int scale_d) {
  asm volatile("{\n.reg .pred p;\nsetp.ne.b32 p, %66, 0;\nwgmma.mma_async.sync.aligned.m64n128k16.f32.bf16.bf16 {%0,%1,%2,%3,%4,%5,%6,%7,%8,%9,%10,%11,%12,%13,%14,%15,%16,%17,%18,%19,%20,%21,%22,%23,%24,%25,%26,%27,%28,%29,%30,%31,%32,%33,%34,%35,%36,%37,%38,%39,%40,%41,%42,%43,%44,%45,%46,%47,%48,%49,%50,%51,%52,%53,%54,%55,%56,%57,%58,%59,%60,%61,%62,%63}, %64, %65, p, 1, 1, %67, %68;\n}"
    : "+f"(d[0]), "+f"(d[1]), "+f"(d[2]), "+f"(d[3]), "+f"(d[4]), "+f"(d[5]), "+f"(d[6]), "+f"(d[7]), "+f"(d[8]), "+f"(d[9]), "+f"(d[10]), "+f"(d[11]), "+f"(d[12]), "+f"(d[13]), "+f"(d[14]), "+f"(d[15]), "+f"(d[16]), "+f"(d[17]), "+f"(d[18]), "+f"(d[19]), "+f"(d[20]), "+f"(d[21]), "+f"(d[22]), "+f"(d[23]), "+f"(d[24]), "+f"(d[25]), "+f"(d[26]), "+f"(d[27]), "+f"(d[28]), "+f"(d[29]), "+f"(d[30]), "+f"(d[31]), "+f"(d[32]), "+f"(d[33]), "+f"(d[34]), "+f"(d[35]), "+f"(d[36]), "+f"(d[37]), "+f"(d[38]), "+f"(d[39]), "+f"(d[40]), "+f"(d[41]), "+f"(d[42]), "+f"(d[43]), "+f"(d[44]), "+f"(d[45]), "+f"(d[46]), "+f"(d[47]), "+f"(d[48]), "+f"(d[49]), "+f"(d[50]), "+f"(d[51]), "+f"(d[52]), "+f"(d[53]), "+f"(d[54]), "+f"(d[55]), "+f"(d[56]), "+f"(d[57]), "+f"(d[58]), "+f"(d[59]), "+f"(d[60]), "+f"(d[61]), "+f"(d[62]), "+f"(d[63])
    : "l"(da), "l"(db), "r"(scale_d), "n"(TA), "n"(TB));
}

__device__ __forceinline__ uint64_t mkdesc(uint32_t lo, uint32_t hi) { uint64_t d; asm("mov.b64 %0, {%1, %2};" : "=l"(d) : "r"(lo), "r"(hi)); return d; }
__device__ __forceinline__ void mbar_init(uint32_t a, int c) { asm volatile("mbarrier.init.shared::cta.b64 [%0], %1;" :: "r"(a), "r"(c)); }
__device__ __forceinline__ void mbar_expect(uint32_t a, uint32_t b) { asm volatile("mbarrier.arrive.expect_tx.shared::cta.b64 _, [%0], %1;" :: "r"(a), "r"(b) : "memory"); }
__device__ __forceinline__ void mbar_arrive(uint32_t a) { asm volatile("mbarrier.arrive.shared::cta.b64 _, [%0];" :: "r"(a) : "memory"); }
#define SPIN_LIMIT (1 << 20)
#define SPIN_FAIL(code) __trap()
__device__ __forceinline__ void mbar_wait(uint32_t a, uint32_t ph) {
    asm volatile("{\n.reg .pred p, q;\n.reg .u32 c;\nmov.u32 c, 0;\n"
                 "W0:\nmbarrier.try_wait.parity.shared::cta.b64 p, [%0], %1;\n@p bra W1;\n"
                 "add.u32 c, c, 1;\nsetp.lt.u32 q, c, %2;\n@q bra W0;\ntrap;\n"
                 "W1:\n}" :: "r"(a), "r"(ph), "n"(4 * SPIN_LIMIT) : "memory");
}
__device__ __forceinline__ void mbar_sleep(uint32_t a, uint32_t ph) {
    asm volatile("{\n.reg .pred p, q;\n.reg .u32 c;\nmov.u32 c, 0;\n"
                 "W0:\nmbarrier.try_wait.parity.shared::cta.b64 p, [%0], %1, 4000;\n@p bra W1;\n"
                 "add.u32 c, c, 1;\nsetp.lt.u32 q, c, %2;\n@q bra W0;\ntrap;\n"
                 "W1:\n}" :: "r"(a), "r"(ph), "n"(SPIN_LIMIT) : "memory");
}
__device__ __forceinline__ void wg_fence() { asm volatile("wgmma.fence.sync.aligned;" ::: "memory"); }
__device__ __forceinline__ void wg_commit() { asm volatile("wgmma.commit_group.sync.aligned;" ::: "memory"); }
template<int N> __device__ __forceinline__ void wg_wait() { asm volatile("wgmma.wait_group.sync.aligned %0;" :: "n"(N) : "memory"); }
__device__ __forceinline__ void bar_sync(int id, int n) { asm volatile("bar.sync %0, %1;" :: "r"(id), "r"(n) : "memory"); }
__device__ __forceinline__ void bar_arrive(int id, int n) { asm volatile("bar.arrive %0, %1;" :: "r"(id), "r"(n) : "memory"); }
__device__ __forceinline__ void fence_async() { asm volatile("fence.proxy.async.global;" ::: "memory"); }
__device__ __forceinline__ void flag_wait(int f, unsigned target) {
    const unsigned* p = &g_flags[f * 8];
    unsigned v;
    #pragma unroll 1
    for (int it = 0; it < SPIN_LIMIT; it++) {
        asm volatile("ld.acquire.gpu.global.u32 %0, [%1];" : "=r"(v) : "l"(p) : "memory");
        if (v >= target) return;
        __nanosleep(20);
    }
    SPIN_FAIL(f);
}
__device__ __forceinline__ void flag_add(int f) { asm volatile("red.release.gpu.global.add.u32 [%0], 1;" :: "l"(&g_flags[f * 8]) : "memory"); }
__device__ __forceinline__ void tma2d(uint32_t dst, const CUtensorMap* m, int c0, int c1, uint32_t bar) {
    asm volatile("cp.async.bulk.tensor.2d.shared::cluster.global.mbarrier::complete_tx::bytes [%0], [%1, {%3, %4}], [%2];"
        :: "r"(dst), "l"(m), "r"(bar), "r"(c0), "r"(c1) : "memory");
}
__device__ __forceinline__ void bulk_ld(uint32_t dst, const void* src, uint32_t bytes, uint32_t bar) {
    asm volatile("cp.async.bulk.shared::cluster.global.mbarrier::complete_tx::bytes [%0], [%1], %2, [%3];"
        :: "r"(dst), "l"(src), "r"(bytes), "r"(bar) : "memory");
}
__device__ __forceinline__ void tma3d_mc(uint32_t dst, const CUtensorMap* m, int c1, int c2, uint32_t bar) {
    asm volatile("cp.async.bulk.tensor.3d.shared::cluster.global.mbarrier::complete_tx::bytes.multicast::cluster [%0], [%1, {0, %3, %4}], [%2], %5;"
        :: "r"(dst), "l"(m), "r"(bar), "r"(c1), "r"(c2), "h"((uint16_t)3) : "memory");
}
__device__ __forceinline__ void bulk_ld_mc(uint32_t dst, const void* src, uint32_t bytes, uint32_t bar) {
    asm volatile("cp.async.bulk.shared::cluster.global.mbarrier::complete_tx::bytes.multicast::cluster [%0], [%1], %2, [%3], %4;"
        :: "r"(dst), "l"(src), "r"(bytes), "r"(bar), "h"((uint16_t)3) : "memory");
}
__device__ __forceinline__ void release2(uint32_t a, uint32_t peer_off) {
    asm volatile("mbarrier.arrive.shared::cta.b64 _, [%0];\nmbarrier.arrive.shared::cluster.b64 _, [%1];" :: "r"(a), "r"(a + peer_off) : "memory");
}
__device__ __forceinline__ void release2n(uint32_t a, uint32_t pa, uint32_t cnt) {
    asm volatile("{\n.reg .pred p;\nsetp.ne.u32 p, %2, 0;\n@p mbarrier.arrive.shared::cta.b64 _, [%0], %2;\n@p mbarrier.arrive.shared::cluster.b64 _, [%1], %2;\n}"
                 :: "r"(a), "r"(pa), "r"(cnt) : "memory");
}
__device__ __forceinline__ bool elect_one() {
    uint32_t p;
    asm volatile("{\n.reg .pred q;\nelect.sync _|q, 0xffffffff;\nselp.u32 %0, 1, 0, q;\n}" : "=r"(p));
    return p != 0;
}
__device__ __forceinline__ void l2_prefetch(const void* src, uint32_t bytes) {
    asm volatile("cp.async.bulk.prefetch.L2.global [%0], %1;" :: "l"(src), "r"(bytes) : "memory");
}
__device__ __forceinline__ uint32_t pack_bf16(float lo, float hi) { uint32_t r; asm("cvt.rn.bf16x2.f32 %0, %1, %2;" : "=r"(r) : "f"(hi), "f"(lo)); return r; }
__device__ __forceinline__ float bf_lo(uint32_t v) { return __uint_as_float(v << 16); }
__device__ __forceinline__ float bf_hi(uint32_t v) { return __uint_as_float(v & 0xFFFF0000u); }
__device__ __forceinline__ float gelu2_tanh(float x) {
    float u = x * fmaf(x * x, 0.0356774081363001f, 0.7978845608028654f), t;
    asm("tanh.approx.f32 %0, %1;" : "=f"(t) : "f"(u));
    return fmaf(x, t, x);
}
#define FENCE_F(a, n) _Pragma("unroll") for (int i_ = 0; i_ < n; i_++) asm volatile("" : "+f"(a[i_]) :: "memory");
#define FENCE_R(a, n) _Pragma("unroll") for (int i_ = 0; i_ < n; i_++) asm volatile("" : "+r"(a[i_]) :: "memory");

__device__ __forceinline__ uint32_t exp2_mufu(float a, float b) {
    float x, y;
    asm("ex2.approx.ftz.f32 %0, %1;" : "=f"(x) : "f"(a));
    asm("ex2.approx.ftz.f32 %0, %1;" : "=f"(y) : "f"(b));
    return pack_bf16(x, y);
}
__device__ __forceinline__ uint32_t exp2_alu(float a, float b, uint32_t half2c) {
    uint32_t L = __byte_perm(__float_as_uint(a), __float_as_uint(b), 0x6521), G, E, r;
    asm("lop3.b32 %0, %1, 0x007F007F, %2, 0xE2;" : "=r"(G) : "r"(L), "r"(half2c));
    asm("lop3.b32 %0, %1, 0x007F007F, %2, 0xB8;" : "=r"(E) : "r"(L), "r"(half2c));
    asm("fma.rn.bf16x2 %0, %1, %2, %3;" : "=r"(r) : "r"(G), "r"(L), "r"(E));
    return r;
}
#define EXPBLK(p, s) _Pragma("unroll") for (int b = 0; b < 8; b++) { \
    if ((PAT >> b) & 1) { p[2*b] = exp2_alu(s[4*b], s[4*b+1], half2c); p[2*b+1] = exp2_alu(s[4*b+2], s[4*b+3], half2c); } \
    else { p[2*b] = exp2_mufu(s[4*b], s[4*b+1]); p[2*b+1] = exp2_mufu(s[4*b+2], s[4*b+3]); } }

struct Ring { uint32_t st, ph; };
template<int NST> __device__ __forceinline__ void ring_next(Ring& r) { if (++r.st == NST) { r.st = 0; r.ph ^= 1; } }

struct OpDesc { uint32_t lo, hi, step, step2, nsplit; };

template<int N, int PART> __device__ __forceinline__ void wgmma_ss(float (&d)[N / 2], uint64_t da, uint64_t db, int sc) {
    if constexpr (N == 160) {
        if constexpr (PART == 0) wgmma_ss_n96<0, 1>(*(float(*)[48])&d[0], da, db, sc);
        else wgmma_ss_n64<0, 1>(*(float(*)[32])&d[48], da, db, sc);
    } else if constexpr (N == 192) {
        if constexpr (PART == 0) wgmma_ss_n128<0, 1>(*(float(*)[64])&d[0], da, db, sc);
        else wgmma_ss_n64<0, 1>(*(float(*)[32])&d[64], da, db, sc);
    } else {
        if constexpr (PART == 0) wgmma_ss_n128<0, 1>(*(float(*)[64])&d[0], da, db, sc);
        else wgmma_ss_n96<0, 1>(*(float(*)[48])&d[64], da, db, sc);
    }
}

struct GemmCtx { Ring r; uint32_t sb16, bar_full, bar_empty, peer_off; bool lead; };

template<int N, int NS, int GB>
__device__ __forceinline__ void gemm_loop(float (&acc)[N / 2], int nkb, int first, OpDesc a, OpDesc b, GemmCtx& c) {
    uint32_t prev = 0;
    #pragma unroll 1
    for (int kb = 0; kb < nkb; kb++) {
        mbar_sleep(c.bar_full + 8 * c.r.st, c.r.ph);
        const uint32_t base = c.sb16 + c.r.st * (GST_BYTES / 16);
        const uint64_t da0 = mkdesc(base + a.lo, a.hi), db0 = mkdesc(base + b.lo, b.hi);
        wg_fence();
        #pragma unroll
        for (int k = 0; k < NS; k++) {
            const uint64_t da = da0 + k * a.step, db = db0 + ((k & 1) * b.step + (k >> 1) * b.step2);
            const int sc = (k > 0) | (kb > 0) | !first;
            wgmma_ss<N, 0>(acc, da, db, sc);
            if constexpr (GB > 0) { wg_commit(); wg_wait<GB - 1>(); }
            wgmma_ss<N, 1>(acc, da, db + b.nsplit, sc);
            if constexpr (GB < 0) {
                if ((k + 1) % (-GB) == 0 || k == NS - 1) {
                    wg_commit(); wg_wait<1>();
                    if (k < -GB && kb > 0 && c.lead) release2(c.bar_empty + 8 * prev, c.peer_off);
                }
            }
            if constexpr (GB > 0) {
                wg_commit(); wg_wait<GB - 1>();
                if (k == (GB - 1) / 2 && kb > 0 && c.lead) release2(c.bar_empty + 8 * prev, c.peer_off);
            }
        }
        if constexpr (GB == 0) {
            wg_commit();
            wg_wait<1>();
            if (kb > 0 && c.lead) release2(c.bar_empty + 8 * prev, c.peer_off);
        }
        prev = c.r.st;
        ring_next<GST>(c.r);
    }
    wg_wait<0>();
    if (c.lead) release2(c.bar_empty + 8 * prev, c.peer_off);
    FENCE_F(acc, N / 2);
}

template<int CNT, int SUBS>
__device__ __forceinline__ void retile_ld(uint4 (&v)[CNT], const __nv_bfloat16* src, int pitch, int ncg, int nkg, int cm0, int cnt, int id) {
    const int sub = id >> 3, row = id & 7;
    #pragma unroll
    for (int i = 0; i < CNT; i++) {
        const int l = sub + i * SUBS, cm = cm0 + l, kg = cm / ncg, cg = cm - kg * ncg;
        if (l < cnt && kg < nkg) v[i] = __ldg((const uint4*)(src + (size_t)(kg * 8 + row) * pitch + cg * 8));
    }
}
template<int NG, int CNT, int SUBS, bool PERM>
__device__ __forceinline__ void retile_st(const uint4 (&v)[CNT], int ncg, int nkg, uint8_t* dst, int cm0, int cnt, int id) {
    const int sub = id >> 3, row = id & 7;
    #pragma unroll
    for (int i = 0; i < CNT; i++) {
        const int l = sub + i * SUBS, cm = cm0 + l, kg = cm / ncg, cg = cm - kg * ncg, tile = cg / NG;
        int kd = kg;
        if (PERM) { const int q = kg / 20, rem = kg - q * 20; kd = rem < 4 ? q * 4 + rem : (rem < 12 ? 12 + q * 8 + rem : 36 + q * 8 + rem); }
        if (l < cnt && kg < nkg) *(uint4*)(dst + (size_t)((tile * nkg + kd) * NG + (cg - tile * NG)) * 128 + row * 16) = v[i];
    }
}

__global__ void __cluster_dims__(2, 1, 1) __launch_bounds__(640, 1) mega_kernel(const __grid_constant__ Params p) {
    extern __shared__ uint8_t smem_raw[];
    const uint32_t sb = ((uint32_t)__cvta_generic_to_shared(smem_raw) + 1023u) & ~1023u;
    uint8_t* sm = smem_raw + (sb - (uint32_t)__cvta_generic_to_shared(smem_raw));
    const uint32_t bar_gfull = sb + SM_MISC, bar_gempty = bar_gfull + 64, bar_kfull = bar_gfull + 128, bar_kempty = bar_gfull + 192;
    float* s_gate = (float*)(sm + SM_MISC + 256);
    float* s_stat = (float*)(sm + SM_MISC + 512);
    float* s_red = (float*)(sm + SM_MISC + 768);
    const int ct = (blockIdx.x >> 2) & 3, rb = ((blockIdx.x >> 4) << 2) | (blockIdx.x & 3);
    const int bid = ct * 32 + rb;
    const int rank = rb & 1;
    const int wg = __shfl_sync(0xffffffffu, threadIdx.x >> 7, 0);
    const int tid = threadIdx.x & 127, w = tid >> 5, lane = tid & 31, g = lane >> 2, t = lane & 3;
    uint32_t peer_off;
    asm("mapa.shared::cluster.u32 %0, %1, %2;" : "=r"(peer_off) : "r"(sb), "r"(rank ^ 1));
    peer_off -= sb;

    if (threadIdx.x >= 576 && threadIdx.x < 580) asm volatile("prefetch.tensormap [%0];" :: "l"(&p.mx + (threadIdx.x - 576)) : "memory");
    if (threadIdx.x == 544) {
        l2_prefetch(p.wq + (size_t)bid * 3200, 6400);
        l2_prefetch(p.win + (size_t)bid * 8640, 17280);
    }
    if (__shfl_sync(0xffffffffu, threadIdx.x >> 5, 0) == 16 && elect_one()) {
        for (int i = 0; i < GST; i++) { mbar_init(bar_gfull + 8 * i, 1); mbar_init(bar_gempty + 8 * i, 8); }
        for (int i = 0; i < KST; i++) { mbar_init(bar_kfull + 8 * i, 1); mbar_init(bar_kempty + 8 * i, 24); }
        mbar_init(bar_kfull + 32, 1); mbar_init(bar_kfull + 40, 1); mbar_init(bar_kfull + 48, 1);
        asm volatile("fence.mbarrier_init.release.cluster;" ::: "memory");
        asm volatile("fence.proxy.async.shared::cta;" ::: "memory");
        if (ct == 3) {
            mbar_arrive(bar_gfull + 24);
            mbar_expect(bar_kfull + 48, 2 * 25600 + 1280);
            bulk_ld(sb + SM_W, p.wk, 25600, bar_kfull + 48);
            bulk_ld(sb + SM_W + 25600, p.wv, 25600, bar_kfull + 48);
            bulk_ld(sb + SM_W + 51200, p.gw, 1280, bar_kfull + 48);
            #pragma unroll 1
            for (int kb = 0; kb < 10; kb++) {
                if ((kb & 3) == 0) mbar_expect(bar_gfull + (kb >> 2) * 8, kb < 8 ? 32768 : 16384);
                tma2d(sb + SM_G + (kb >> 2) * GST_BYTES + (kb & 3) * 8192, &p.mx, kb * 64, rb * 64, bar_gfull + (kb >> 2) * 8);
            }
        }
    }
    asm volatile("barrier.cluster.arrive.relaxed;\nbarrier.cluster.wait.acquire;" ::: "memory");

    if (wg == 4) {
        asm volatile("setmaxnreg.dec.sync.aligned.u32 24;");
        const int wu = __shfl_sync(0xffffffffu, w, 0);
        static_assert(GST == 4, "ring indices are derived from a running stage counter");
        #define STG_ADDR(n) (sb + SM_G + ((n) & 3) * GST_BYTES)
        #define STG_FULL(n) (bar_gfull + ((n) & 3) * 8)
        #define STG_WAIT(n) mbar_sleep(bar_gempty + ((n) & 3) * 8, (((n) >> 2) & 1) ^ 1)
        const uint32_t n0 = ct == 3 ? 4 : 0;
        if (wu == 0) {
            uint32_t n = n0;
            if (elect_one()) {
                #pragma unroll 1
                for (int kb = 0; kb < 10; kb++, n++) {
                    STG_WAIT(n);
                    mbar_expect(STG_FULL(n), 8192 + 20480);
                    tma3d_mc(STG_ADDR(n) + 8192 + rank * 10240, &p.mwq, kb * 64 + rank * 32, 5 * ct, STG_FULL(n));
                }
                #pragma unroll 1
                for (int i = 0; i < 20; i++, n++) {
                    STG_WAIT(n);
                    mbar_expect(STG_FULL(n), 8192 + 28672);
                    tma3d_mc(STG_ADDR(n) + 8192 + rank * 14336, &p.mwin, (i < 10 ? i : i - 10) * 64 + rank * 32, (i < 10 ? 27 : 0) + 7 * ct, STG_FULL(n));
                }
            }
            __syncwarp();
            #pragma unroll 1
            for (int it = 0; ; it++) {
                unsigned v;
                asm volatile("ld.acquire.gpu.global.u32 %0, [%1];" : "=r"(v) : "l"(&g_flags[(F_Z2 + lane * 4 + ct) * 8]) : "memory");
                if (__all_sync(0xffffffffu, v != 0)) break;
                if (it > SPIN_LIMIT) SPIN_FAIL(F_Z2);
                __nanosleep(20);
            }
            if (elect_one()) {
                n = n0 + 30;
                fence_async();
                const uint8_t* src = g_z2n + (size_t)ct * 32 * 28672 + rank * 14336;
                #pragma unroll 1
                for (int kb = 0; kb < 32; kb++, n++, src += 28672) {
                    STG_WAIT(n);
                    mbar_expect(STG_FULL(n), 8192 + 28672);
                    bulk_ld_mc(STG_ADDR(n) + 8192 + rank * 14336, src, 14336, STG_FULL(n));
                }
                flag_wait(F_WR, 96);
                fence_async();
                n++;
                #pragma unroll 1
                for (int i = 0; i < 2; i++, n++) {
                    STG_WAIT(n);
                    mbar_expect(STG_FULL(n), 28672);
                    bulk_ld_mc(STG_ADDR(n) + 8192 + rank * 10240, g_wot + (size_t)(ct * 80 + i * 8) * 2560 + rank * 10240, 10240, STG_FULL(n));
                }
                uint32_t k0 = 28 * ct + rank * 4;
                #pragma unroll 1
                for (int i = 0; i < 14; i++, n++) {
                    const uint32_t nk = i == 13 ? 2 : 4;
                    if (i == 13) k0 -= rank * 2;
                    if (k0 >= 108) k0 -= 108;
                    STG_WAIT(n);
                    mbar_expect(STG_FULL(n), nk * 2 * (2560 + 1024));
                    bulk_ld_mc(STG_ADDR(n) + 8192 + rank * nk * 2560, g_woutt + (size_t)(ct * 108 + k0) * 2560, nk * 2560, STG_FULL(n));
                    k0 += 8;
                }
                #pragma unroll 1
                for (int i = 2; i < 10; i++, n++) {
                    STG_WAIT(n);
                    mbar_expect(STG_FULL(n), 28672);
                    bulk_ld_mc(STG_ADDR(n) + 8192 + rank * 10240, g_wot + (size_t)(ct * 80 + i * 8) * 2560 + rank * 10240, 10240, STG_FULL(n));
                }
            }
        } else if (wu == 3) {
            if (elect_one()) {
                uint32_t n = n0;
                #pragma unroll 1
                for (int j = 0; j < 3; j++) {
                    #pragma unroll 1
                    for (int kb = 0; kb < 10; kb++, n++) {
                        STG_WAIT(n);
                        tma2d(STG_ADDR(n), &p.mx, kb * 64, rb * 64, STG_FULL(n));
                    }
                }
                #define STASH_STAGE(which) { STG_WAIT(n); fence_async(); mbar_expect(STG_FULL(n), 28672); \
                    bulk_ld(STG_ADDR(n), g_z1 + (size_t)((which) * NCTA + bid) * 1792, 28672, STG_FULL(n)); n++; }
                #pragma unroll 1
                for (int kb = 0; kb < 32; kb++, n++) {
                    STG_WAIT(n);
                    tma2d(STG_ADDR(n), &p.mwsp, kb * 64, rb * 64, STG_FULL(n));
                }
                STASH_STAGE(0)
                const uint8_t* op = g_op + (size_t)rb * 80 * 1024;
                const uint8_t* hp = g_hp + (size_t)rb * 108 * 1024;
                flag_wait(F_O + rb * 3, 4);
                fence_async();
                #pragma unroll 1
                for (int i = 0; i < 2; i++, n++) { STG_WAIT(n); bulk_ld(STG_ADDR(n), op + i * 8192, 8192, STG_FULL(n)); }
                mbar_sleep(bar_kfull + 40, 0);
                fence_async();
                uint32_t k0 = 28 * ct;
                #pragma unroll 1
                for (int i = 0; i < 14; i++, n++) {
                    if (i == 3) { flag_wait(F_H + rb, 4); fence_async(); }
                    STG_WAIT(n);
                    const uint32_t nb = (i == 13 || k0 == 104) ? 4096 : 8192;
                    bulk_ld(STG_ADDR(n), hp + k0 * 1024, nb, STG_FULL(n));
                    if (k0 == 104 && i != 13) bulk_ld(STG_ADDR(n) + 4096, hp, 4096, STG_FULL(n));
                    k0 += 8; if (k0 >= 108) k0 -= 108;
                }
                #pragma unroll 1
                for (int i = 2; i < 10; i++, n++) {
                    if (i == 2 || i == 6) { flag_wait(F_O + rb * 3 + (i == 2 ? 1 : 2), i == 2 ? 4 : 12); fence_async(); }
                    STG_WAIT(n);
                    bulk_ld(STG_ADDR(n), op + i * 8192, 8192, STG_FULL(n));
                }
            }
            __syncwarp();
            unsigned d = 0;
            if (lane == 0) d = atomicAdd(&g_flags[F_DONE * 8], 1u);
            if (__shfl_sync(0xffffffffu, d, 0) == NCTA - 1) {
                #pragma unroll
                for (int i = 0; i < (F_NUM + 31) / 32; i++) if (i * 32 + lane < F_NUM) g_flags[(i * 32 + lane) * 8] = 0;
            }
        } else if (wu == 1) {
            if (elect_one()) {
                flag_wait(F_KV, 32);
                asm volatile("fence.proxy.async.global;" ::: "memory");
                mbar_expect(bar_kfull + 32, 6144 + 512);
                bulk_ld(sb + SM_KV + 3 * KST_BYTES + 6144, g_kv + 31 * 6144, 6144, bar_kfull + 32);
                bulk_ld(sb + SM_MISC + 512, g_kvmax, 256, bar_kfull + 32);
                bulk_ld(sb + SM_MISC + 256, g_gate + rb * 64, 256, bar_kfull + 32);
                #pragma unroll 1
                for (int i = 0; i < 48; i++) {
                    const uint32_t st = i & 3;
                    if (i >= 3) mbar_sleep(bar_kempty + 8 * st, (((i + 1) >> 2) & 1) ^ 1);
                    mbar_expect(bar_kfull + 8 * st, KST_BYTES);
                    bulk_ld_mc(sb + SM_KV + st * KST_BYTES + rank * 6144, g_kv + (i & 15) * KST_BYTES + rank * 6144, 6144, bar_kfull + 8 * st);
                    if (i == 19 || i == 35) flag_add(F_O + rb * 3 + (i == 35));
                }
            }
        } else {
            if (ct == 3) {
                bar_sync(10, 160);
                if (lane < 2) {
                    const float* r = s_red + 8 + 4 * lane;
                    g_kvmax[lane * 32 + rb] = __uint_as_float(max(max(__float_as_uint(r[0]), __float_as_uint(r[1])), max(__float_as_uint(r[2]), __float_as_uint(r[3]))));
                }
                __syncwarp();
                if (elect_one()) flag_add(F_KV);
                __syncwarp();
            }
            bar_sync(10, 160);
            if (elect_one()) { flag_add(F_H + rb); mbar_arrive(bar_kfull + 40); }
        }
    } else if (wg == 3) {
        asm volatile("setmaxnreg.inc.sync.aligned.u32 144;");
        GemmCtx c{{0, 0}, ((sb + SM_G) & 0x3FFFFu) >> 4, bar_gfull, bar_gempty, peer_off, lane == 0};
        const OpDesc a_sw{0u, 64u | (1u << 30), 2u, 0u, 0u};
        const OpDesc a_t{64u << 16, 8u, 128u, 0u, 0u};
        const OpDesc b_q{512u | (128u << 16), 32u | (2u << 30), 64u, 640u, 384u};
        const OpDesc b_w{512u | (128u << 16), 32u | (2u << 30), 64u, 896u, 512u};
        const OpDesc b_z{512u | (224u << 16), 8u, 448u, 896u, 128u};
        const OpDesc b_o{512u | (160u << 16), 8u, 320u, 640u, 96u};
        const int r0 = 16 * w + g;
        if (ct == 3) {
            float ex[24];
            const uint32_t exlo = (((sb + SM_KV) & 0x3FFFFu) >> 4) | (48u << 16);
            bar_sync(1, 512);
            #pragma unroll 1
            for (int kb = 0; kb < 10; kb++) {
                if ((kb & 3) == 0) mbar_wait(bar_gfull + 8 * (kb >> 2), 0);
                const uint32_t base = c.sb16 + (kb >> 2) * (GST_BYTES / 16) + (kb & 3) * 512;
                wg_fence();
                #pragma unroll
                for (int k = 0; k < 4; k++) wgmma_ss_n48<0, 1>(ex, mkdesc(base + 2 * k, a_sw.hi), mkdesc(exlo + (kb * 4 + k) * 96, 8), (k > 0) | (kb > 0));
                wg_commit();
            }
            wg_wait<0>();
            FENCE_F(ex, 24);
            if (lane < 4) release2(bar_gempty + 8 * lane, peer_off);
            c.r.ph = 1;
            uint8_t* dk = g_kv + ((rb + 31) & 31) * 6144 + 2 * w * 384 + g * 16 + t * 4;
            uint8_t* dv = g_kv + rb * 6144 + 3072 + 2 * w * 384 + g * 16 + t * 4;
            uint32_t mk = 0, mv = 0;
            #pragma unroll
            for (int hi = 0; hi < 2; hi++) {
                const bool alu = (PAT >> (2 * w + hi)) & 1;
                float n2 = 0.f;
                #pragma unroll
                for (int j = 0; j < 3; j++) {
                    uint32_t v = pack_bf16(ex[4 * j + 2 * hi], ex[4 * j + 2 * hi + 1]);
                    const float a = bf_lo(v), b = bf_hi(v);
                    n2 = fmaf(a, a, fmaf(b, b, n2));
                    if (alu) v = pack_bf16(2.f * a, 2.f * b);
                    if (j == 2 && t == 2) v = alu ? 0x3C004446u : 0x3CF14159u;
                    *(uint32_t*)(dk + hi * 384 + j * 128) = v;
                    v = pack_bf16(ex[12 + 4 * j + 2 * hi], ex[12 + 4 * j + 2 * hi + 1]);
                    if (j < 2 || t < 2) mv = max(mv, max((v << 16) & 0x7FFF0000u, v & 0x7FFF0000u));
                    if (j == 2 && t == 3) {
                        g_gate[rb * 64 + r0 + 8 * hi] = 1.f / (1.f + __expf(-ex[20 + 2 * hi]));
                        v = 0u;
                    }
                    if (j == 2 && t == 2) v = 0x00003F80u;
                    *(uint32_t*)(dv + hi * 384 + j * 128) = v;
                }
                n2 += __shfl_xor_sync(0xffffffffu, n2, 1); n2 += __shfl_xor_sync(0xffffffffu, n2, 2);
                mk = max(mk, __float_as_uint(n2) & 0x7FFFFFFFu);
            }
            mk = __reduce_max_sync(0xffffffffu, mk); mv = __reduce_max_sync(0xffffffffu, mv);
            if (lane == 0) { s_red[8 + w] = __uint_as_float(mk); s_red[12 + w] = __uint_as_float(mv); }
            bar_arrive(10, 160);
        }
        {
            float acc[80];
            gemm_loop<160, 4, 0>(acc, 10, 1, a_sw, b_q, c);
            uint8_t* qs = sm + SM_Q + 2 * w * 128 + g * 16;
            #pragma unroll
            for (int j = 0; j < 20; j++) {
                const int h0 = (8 * j) / 20, d0 = (8 * j) % 20, d = d0 + 2 * t;
                const int off = d < 20 ? h0 * 3072 + (d >> 3) * 1024 + (d & 7) * 2 : (h0 + 1) * 3072 + (d - 20) * 2;
                *(uint32_t*)(qs + off) = pack_bf16(acc[4 * j] * 0.3225964182229561f, acc[4 * j + 1] * 0.3225964182229561f);
                *(uint32_t*)(qs + off + 128) = pack_bf16(acc[4 * j + 2] * 0.3225964182229561f, acc[4 * j + 3] * 0.3225964182229561f);
            }
            asm volatile("fence.proxy.async.shared::cta;" ::: "memory");
            bar_arrive(2, 384);
            bar_arrive(13, 256);
        }
        {
            float acc[112];
            #pragma unroll
            for (int i = 96; i < 112; i++) acc[i] = 0.f;
            #define GEMM_Z(GBX, nkb, first, bd) { if (ct == 3) gemm_loop<192, 4, GBX>(*(float(*)[96])&acc[0], nkb, first, a_sw, bd, c); \
                                                  else gemm_loop<224, 4, GBX>(acc, nkb, first, a_sw, bd, c); }
            GEMM_Z(GB2, 10, 1, b_w)
            uint4* z1p = g_z1 + (size_t)bid * 14 * 128 + tid;
            {
                float s0 = 0.f, q0 = 0.f, s1 = 0.f, q1 = 0.f;
                #pragma unroll
                for (int j = 0; j < 14; j++) {
                    float y[8];
                    #pragma unroll
                    for (int i = 0; i < 8; i++) y[i] = gelu2_tanh(acc[8 * j + i]);
                    s0 += (y[0] + y[1]) + (y[4] + y[5]); q0 = fmaf(y[0], y[0], fmaf(y[1], y[1], fmaf(y[4], y[4], fmaf(y[5], y[5], q0))));
                    s1 += (y[2] + y[3]) + (y[6] + y[7]); q1 = fmaf(y[2], y[2], fmaf(y[3], y[3], fmaf(y[6], y[6], fmaf(y[7], y[7], q1))));
                    z1p[(NCTA * 14 + j) * 128] = make_uint4(pack_bf16(y[0], y[1]), pack_bf16(y[2], y[3]), pack_bf16(y[4], y[5]), pack_bf16(y[6], y[7]));
                }
                #pragma unroll
                for (int o = 1; o <= 2; o <<= 1) {
                    s0 += __shfl_xor_sync(0xffffffffu, s0, o); q0 += __shfl_xor_sync(0xffffffffu, q0, o);
                    s1 += __shfl_xor_sync(0xffffffffu, s1, o); q1 += __shfl_xor_sync(0xffffffffu, q1, o);
                }
                if (t < 2) asm volatile("st.relaxed.gpu.global.b64 [%0], %1;" :: "l"(&g_part[(rb * 4 + ct) * 64 + r0 + 8 * t]),
                                        "l"(mkdesc(__float_as_uint(t ? s1 : s0), __float_as_uint(t ? q1 : q0) | 0x80000000u)) : "memory");
            }
            bar_arrive(11, 256);
            GEMM_Z(GB3, 10, 1, b_w)
            #pragma unroll
            for (int j = 0; j < 14; j++)
                z1p[j * 128] = make_uint4(pack_bf16(gelu2_tanh(acc[8 * j]), gelu2_tanh(acc[8 * j + 1])), pack_bf16(gelu2_tanh(acc[8 * j + 2]), gelu2_tanh(acc[8 * j + 3])),
                                          pack_bf16(gelu2_tanh(acc[8 * j + 4]), gelu2_tanh(acc[8 * j + 5])), pack_bf16(gelu2_tanh(acc[8 * j + 6]), gelu2_tanh(acc[8 * j + 7])));
            const float b0 = __bfloat162float(p.bsp[rb * 64 + r0]), b1 = __bfloat162float(p.bsp[rb * 64 + r0 + 8]);
            GEMM_Z(GB4, 32, 1, b_z)
            bar_sync(8, 512);
            const float g0 = 0.5f - 0.5f * s_gate[r0], g1 = 0.5f - 0.5f * s_gate[r0 + 8];
            {
                mbar_wait(c.bar_full + 8 * c.r.st, c.r.ph);
                const uint4* zs = (const uint4*)(sm + SM_G + c.r.st * GST_BYTES) + tid;
                uint8_t* dst = g_hp + (size_t)((rb * 108 + 28 * ct) * 8 + 2 * w) * 128 + g * 16 + t * 4;
                const float e0 = b0 * g0, e1 = b1 * g1;
                #pragma unroll
                for (int j = 0; j < 14; j++) {
                    if (j < 12 || ct < 3) {
                        const uint4 v = zs[j * 128];
                        *(uint32_t*)(dst + (2 * j) * 1024) = pack_bf16(fmaf(acc[8 * j], g0, e0) * bf_lo(v.x), fmaf(acc[8 * j + 1], g0, e0) * bf_hi(v.x));
                        *(uint32_t*)(dst + (2 * j) * 1024 + 128) = pack_bf16(fmaf(acc[8 * j + 2], g1, e1) * bf_lo(v.y), fmaf(acc[8 * j + 3], g1, e1) * bf_hi(v.y));
                        *(uint32_t*)(dst + (2 * j + 1) * 1024) = pack_bf16(fmaf(acc[8 * j + 4], g0, e0) * bf_lo(v.z), fmaf(acc[8 * j + 5], g0, e0) * bf_hi(v.z));
                        *(uint32_t*)(dst + (2 * j + 1) * 1024 + 128) = pack_bf16(fmaf(acc[8 * j + 6], g1, e1) * bf_lo(v.w), fmaf(acc[8 * j + 7], g1, e1) * bf_hi(v.w));
                    }
                }
                __syncwarp();
                if (c.lead) release2(c.bar_empty + 8 * c.r.st, c.peer_off);
                ring_next<GST>(c.r);
            }
            bar_arrive(10, 160);
        }
        {
            float acc[80];
            gemm_loop<160, 4, GB5>(acc, 15, 1, a_t, b_o, c);
            gemm_loop<160, 2, GB5>(acc, 1, 0, a_t, b_o, c);
            gemm_loop<160, 4, GB5>(acc, 4, 0, a_t, b_o, c);
            if (tid < 64) g_part[(rb * 4 + ct) * 64 + tid] = 0ull;
            gemm_loop<160, 4, 0>(acc, 4, 0, a_t, b_o, c);
            uint32_t* os = (uint32_t*)(sm + SM_Q) + r0 * (QS_PITCH / 2) + t;
            #pragma unroll
            for (int j = 0; j < 20; j++) {
                os[4 * j] = pack_bf16(acc[4 * j], acc[4 * j + 1]);
                os[8 * (QS_PITCH / 2) + 4 * j] = pack_bf16(acc[4 * j + 2], acc[4 * j + 3]);
            }
            asm volatile("fence.proxy.async.shared::cta;" ::: "memory");
            __syncwarp();
            if (lane < 16) {
                const int row = 16 * w + lane;
                asm volatile("cp.async.bulk.global.shared::cta.bulk_group [%0], [%1], 320;"
                             :: "l"(p.out + (size_t)(rb * 64 + row) * DM + 160 * ct), "r"(sb + SM_Q + row * (QS_PITCH * 2)) : "memory");
                asm volatile("cp.async.bulk.commit_group;\ncp.async.bulk.wait_group.read 0;" ::: "memory");
            }
            __syncwarp();
            asm volatile("barrier.cluster.arrive.relaxed;\nbarrier.cluster.wait;" ::: "memory");
        }
    } else {
        asm volatile("setmaxnreg.inc.sync.aligned.u32 104;");
        const int atid = threadIdx.x;
        {
            *(uint2*)(sm + SM_Q + 8 * 3072 + (atid & 127) * 8) = make_uint2(0u, 0u);
            if (ct < 3) {
                uint4 w1[2], w2[2];
                const int c1 = bid * 67, c2 = bid * 90;
                retile_ld<2, 48>(w1, p.wo, DM, 80, 80, c1, 67, atid);
                retile_ld<2, 48>(w2, p.wout, DM, 80, 108, c2, 90, atid);
                retile_st<20, 2, 48, true>(w1, 80, 80, g_wot, c1, 67, atid);
                retile_st<20, 2, 48, false>(w2, 80, 108, g_woutt, c2, 90, atid);
                bar_sync(9, 384);
                if (atid == 256) flag_add(F_WR);
            } else {
                mbar_wait(bar_kfull + 48, 0);
                #pragma unroll 2
                for (int e = atid; e < 1280; e += 384) {
                    const int m = e >= 640, k = e - m * 640;
                    const uint2* src = (const uint2*)(sm + SM_W + e * 40);
                    const uint2 a = src[0], b = src[1], c = src[2], d = src[3], f = src[4];
                    const uint32_t gt = m ? *(const unsigned short*)(sm + SM_W + 51200 + k * 2) : 0u;
                    uint4* dst = (uint4*)(sm + SM_KV + (k >> 3) * 768 + (k & 7) * 16 + m * 384);
                    dst[0] = make_uint4(a.x, a.y, b.x, b.y); dst[8] = make_uint4(c.x, c.y, d.x, d.y); dst[16] = make_uint4(f.x, f.y, 0u, gt);
                }
                asm volatile("fence.proxy.async.shared::cta;" ::: "memory");
                bar_arrive(1, 512);
            }
        }
        const uint32_t half2c = *(const volatile uint32_t*)&g_const[0];
        if (wg == 2) {
            const int r0 = 16 * w + g;
            uint4* z1p = g_z1 + (size_t)bid * 14 * 128 + tid;
            uint4 v[14];
            bar_sync(11, 256);
            #pragma unroll
            for (int j = 0; j < 14; j++) v[j] = __ldcg(z1p + (NCTA * 14 + j) * 128);
            float s0, q0, s1, q1;
            {
                unsigned long long a, b;
                const unsigned long long* pa_ = &g_part[(rb * 4 + t) * 64 + r0];
                #pragma unroll 1
                for (int it = 0; ; it++) {
                    asm volatile("ld.relaxed.gpu.global.b64 %0, [%1];" : "=l"(a) : "l"(pa_) : "memory");
                    asm volatile("ld.relaxed.gpu.global.b64 %0, [%1];" : "=l"(b) : "l"(pa_ + 8) : "memory");
                    if (__all_sync(0xffffffffu, ((a & b) >> 63) != 0)) break;
                    if (it > SPIN_LIMIT) SPIN_FAIL(0x7000);
                    __nanosleep(100);
                }
                s0 = __uint_as_float((uint32_t)a); q0 = __uint_as_float((uint32_t)(a >> 32) & 0x7FFFFFFFu);
                s1 = __uint_as_float((uint32_t)b); q1 = __uint_as_float((uint32_t)(b >> 32) & 0x7FFFFFFFu);
                #pragma unroll
                for (int o = 1; o <= 2; o <<= 1) {
                    s0 += __shfl_xor_sync(0xffffffffu, s0, o); q0 += __shfl_xor_sync(0xffffffffu, q0, o);
                    s1 += __shfl_xor_sync(0xffffffffu, s1, o); q1 += __shfl_xor_sync(0xffffffffu, q1, o);
                }
            }
            const float m0 = s0 * (1.f / FH), m1 = s1 * (1.f / FH);
            const float rs0 = rsqrtf(fmaxf(q0 * (1.f / FH) - m0 * m0, 0.f) + 4e-5f), rs1 = rsqrtf(fmaxf(q1 * (1.f / FH) - m1 * m1, 0.f) + 4e-5f);
            const float c0 = -m0 * rs0, c1 = -m1 * rs1;
            uint8_t* dst = g_z2n + (size_t)(ct * 32 + rb) * 28672 + (2 * w) * 3584 + g * 16 + t * 4;
            #pragma unroll
            for (int j = 0; j < 14; j++) {
                *(uint32_t*)(dst + 2 * j * 128) = pack_bf16(fmaf(bf_lo(v[j].x), rs0, c0), fmaf(bf_hi(v[j].x), rs0, c0));
                *(uint32_t*)(dst + 3584 + 2 * j * 128) = pack_bf16(fmaf(bf_lo(v[j].y), rs1, c1), fmaf(bf_hi(v[j].y), rs1, c1));
                *(uint32_t*)(dst + (2 * j + 1) * 128) = pack_bf16(fmaf(bf_lo(v[j].z), rs0, c0), fmaf(bf_hi(v[j].z), rs0, c0));
                *(uint32_t*)(dst + 3584 + (2 * j + 1) * 128) = pack_bf16(fmaf(bf_lo(v[j].w), rs1, c1), fmaf(bf_hi(v[j].w), rs1, c1));
            }
            bar_sync(6, 128);
            if (tid == 0) flag_add(F_Z2 + rb * 4 + ct);
        }
        if (wg == 2) bar_sync(13, 256); else bar_sync(2, 384);
        const int p0 = wg == 2 ? 1 : 0;
        #define HEAD(ps) ((ps) == 0 ? wg : 3 * (ps) - 1 + wg)
        uint32_t qmax2 = 0;
        #pragma unroll 1
        for (int i = p0 + (tid >> 6); i < 3; i += 2) {
            uint8_t* qrow = sm + SM_Q + HEAD(i) * 3072 + (tid & 63) * 16;
            const uint4 a = *(const uint4*)qrow, b = *(const uint4*)(qrow + 1024);
            const uint2 c = *(const uint2*)(qrow + 2048);
            #define SQ(v) (bf_lo(v) * bf_lo(v) + bf_hi(v) * bf_hi(v))
            const float n = SQ(a.x) + SQ(a.y) + SQ(a.z) + SQ(a.w) + SQ(b.x) + SQ(b.y) + SQ(b.z) + SQ(b.w) + SQ(c.x) + SQ(c.y);
            qmax2 = max(qmax2, __float_as_uint(n) & 0x7FFFFFFFu);
            *(uint2*)(qrow + 2048 + 8) = make_uint2(0x3F803F80u, 0u);
        }
        asm volatile("fence.proxy.async.shared::cta;" ::: "memory");
        mbar_sleep(bar_kfull + 32, 0);
        bar_arrive(8, 512);
        uint32_t safe;
        {
            const float kmax2 = __uint_as_float(__reduce_max_sync(0xffffffffu, __float_as_uint(s_stat[lane])));
            const int ev = (int)(__reduce_max_sync(0xffffffffu, __float_as_uint(s_stat[32 + lane])) >> 23) - 126;
            const float bmax = (float)min(102 - max(ev, 1), 100 + ev);
            const bool ok = bmax > 0.f && __uint_as_float(qmax2) * kmax2 <= bmax * bmax;
            asm volatile("{\n.reg .pred p, q;\nsetp.ne.u32 p, %1, 0;\nbarrier.red.and.pred.aligned q, %2, 128, p;\nselp.u32 %0, 1, 0, q;\n}"
                         : "=r"(safe) : "r"((uint32_t)ok), "r"(4 + wg) : "memory");
            safe = __shfl_sync(0xffffffffu, safe, 0);
            if (!safe) {
                #pragma unroll 1
                for (int i = p0 + (tid >> 6); i < 3; i += 2) *(uint2*)(sm + SM_Q + HEAD(i) * 3072 + (tid & 63) * 16 + 2048 + 8) = make_uint2(0u, 0u);
                asm volatile("fence.proxy.async.shared::cta;" ::: "memory");
                bar_sync(4 + wg, 128);
            }
        }
        const uint32_t kv16 = ((sb + SM_KV) & 0x3FFFFu) >> 4;
        constexpr uint32_t KLBO = 8u << 16, KHI = 24u, VLBO = (24u << 16) + 192u, VHI = 8u;
        const bool lead = lane == 0;
        const int r0 = 16 * w + g;
        static_assert(KST == 4, "ring phases below assume 4 stages");
        if (wg == 2) {
            bar_sync(14, 256);
            mbar_wait(bar_kfull + 24, 1);
        }
        const uint32_t q16 = ((sb + SM_Q) & 0x3FFFFu) >> 4;
        uint64_t qa = mkdesc(q16 + HEAD(p0) * 192 + (64u << 16), 8), qb = mkdesc(q16 + HEAD(p0) * 192 + 128 + ((uint32_t)(1536 - 128 - HEAD(p0) * 192) << 16), 8);
        #define NEXT_HEAD(ps) { const uint32_t d_ = (ps) == 0 ? 384 : 576; qa += d_; qb += (uint64_t)d_ - ((uint64_t)d_ << 16); }
        const uint64_t dk = mkdesc(kv16 + KLBO, KHI), dv = mkdesc(kv16 + VLBO, VHI);
        const uint32_t kep = bar_kempty + peer_off;
        uint32_t rc = lead ? (wg == 0 ? 2 : 1) : 0;
        float o[12];
        #pragma unroll
        for (int i = 0; i < 12; i++) o[i] = 0.f;
        float s[32]; uint32_t pa[16], pb[16];
        FENCE_F(o, 12);
        #define QK(off) wgmma_ss_n64<0, 0>(s, qa, dk + (off), 0); wgmma_ss_n64<0, 0>(s, qb, dk + (off) + 16, 1);
        #define PV(pp, off) wgmma_rs_n24<1>(o, pp[0], pp[1], pp[2], pp[3], dv + (off), 1); wgmma_rs_n24<1>(o, pp[4], pp[5], pp[6], pp[7], dv + (off) + 48, 1); \
                            wgmma_rs_n24<1>(o, pp[8], pp[9], pp[10], pp[11], dv + (off) + 96, 1); wgmma_rs_n24<1>(o, pp[12], pp[13], pp[14], pp[15], dv + (off) + 144, 1);
        #define STORE_O(h) { \
            const float l0 = __shfl_sync(0xffffffffu, o[8], (lane & ~3) | 2), l1 = __shfl_sync(0xffffffffu, o[10], (lane & ~3) | 2); \
            const float i0 = __fdividef(s_gate[r0], l0), i1 = __fdividef(s_gate[r0 + 8], l1);        \
            _Pragma("unroll") for (int b = 0; b < 3; b++) { \
                if (b < 2 || t < 2) { \
                    const int cq = 20 * (h) + 8 * b + 2 * t, col = cq < 32 ? ct * 32 + cq : (cq < 96 ? 96 + ct * 64 + cq : 288 + ct * 64 + cq); \
                    uint8_t* dst = g_op + (size_t)((rb * 80 + (col >> 3)) * 8 + 2 * w) * 128 + g * 16 + (col & 7) * 2; \
                    *(uint32_t*)dst = pack_bf16(o[4 * b] * i0, o[4 * b + 1] * i0); \
                    *(uint32_t*)(dst + 128) = pack_bf16(o[4 * b + 2] * i1, o[4 * b + 3] * i1); \
                } \
            } \
            _Pragma("unroll") for (int i = 0; i < 12; i++) o[i] = 0.f; \
            FENCE_F(o, 12); \
 \
            __syncwarp(); }
        if (safe) {
            wg_fence();
            QK(3 * 768 + 384)
            wg_commit();
            wg_wait<0>();
            FENCE_F(s, 32);
            release2n(bar_kempty + 24, kep + 24, rc);
            EXPBLK(pa, s);
            FENCE_R(pa, 16);
            #define HALF(off, pin, pout) \
                wg_fence(); \
                QK(off) \
                wg_commit(); \
                PV(pin, off) \
                wg_commit(); \
                wg_wait<1>(); \
                FENCE_F(s, 32); \
                EXPBLK(pout, s); \
                FENCE_R(pout, 16); \
                wg_wait<0>();
            #pragma unroll 1
            for (int J4 = 4 * p0; J4 < 12; J4++) {
                const uint32_t ph = J4 & 1;
                #pragma unroll
                for (int st = 0; st < 4; st++) {
                    mbar_wait(bar_kfull + 8 * st, ph);
                    if (st == 3 && J4 == 3 && wg == 0) bar_arrive(14, 256);
                    HALF(st * 768, pa, pb)
                    if (st == 3 && (J4 & 3) == 3 && J4 < 11) NEXT_HEAD(J4 >> 2)
                    HALF(st * 768 + 384, pb, pa)
                    if (st < 3) release2n(bar_kempty + 8 * st, kep + 8 * st, rc);
                }
                if ((J4 & 3) == 3) {
                    FENCE_F(o, 12);
                    STORE_O(HEAD(J4 >> 2))
                    rc = lead ? 1 : 0;
                }
                release2n(bar_kempty + 24, kep + 24, rc);
            }
        } else {
            float m0 = -INFINITY, m1 = -INFINITY;
            #pragma unroll 1
            for (int u = 32 * p0; u < 96; u++) {
                const int J = u >> 1;
                if ((u & 1) == 0) mbar_wait(bar_kfull + 8 * (J & 3), (J >> 2) & 1);
                if (u == 30 && wg == 0) bar_arrive(14, 256);
                wg_fence();
                QK(((u + 7) & 7) * 384)
                wg_commit();
                wg_wait<0>();
                FENCE_F(s, 32);
                float x0 = m0, x1 = m1;
                #pragma unroll
                for (int b = 0; b < 8; b++) {
                    const float f = ((PAT >> b) & 1) ? 0.5f : 1.f;
                    s[4 * b] *= f; s[4 * b + 1] *= f; s[4 * b + 2] *= f; s[4 * b + 3] *= f;
                    x0 = fmaxf(x0, fmaxf(s[4 * b], s[4 * b + 1])); x1 = fmaxf(x1, fmaxf(s[4 * b + 2], s[4 * b + 3]));
                }
                x0 = fmaxf(x0, __shfl_xor_sync(0xffffffffu, x0, 1)); x0 = fmaxf(x0, __shfl_xor_sync(0xffffffffu, x0, 2));
                x1 = fmaxf(x1, __shfl_xor_sync(0xffffffffu, x1, 1)); x1 = fmaxf(x1, __shfl_xor_sync(0xffffffffu, x1, 2));
                const float f0 = exp2f(m0 - x0), f1 = exp2f(m1 - x1);
                m0 = x0; m1 = x1;
                #pragma unroll
                for (int b = 0; b < 3; b++) { o[4 * b] *= f0; o[4 * b + 1] *= f0; o[4 * b + 2] *= f1; o[4 * b + 3] *= f1; }
                #pragma unroll
                for (int b = 0; b < 8; b++) {
                    pa[2 * b] = exp2_mufu(s[4 * b] - m0, s[4 * b + 1] - m0);
                    pa[2 * b + 1] = exp2_mufu(s[4 * b + 2] - m1, s[4 * b + 3] - m1);
                }
                FENCE_R(pa, 16); FENCE_F(o, 12);
                wg_fence();
                PV(pa, (u & 7) * 384)
                wg_commit();
                wg_wait<0>();
                FENCE_F(o, 12);
                if ((u & 1) == 0) release2n(bar_kempty + 8 * ((J + 3) & 3), kep + 8 * ((J + 3) & 3), rc);
                if ((u & 31) == 31) {
                    STORE_O(HEAD(u >> 5))
                    m0 = -INFINITY; m1 = -INFINITY;
                    NEXT_HEAD(u >> 5)
                    rc = lead ? 1 : 0;
                }
            }
        }
        bar_sync(4 + wg, 128);
        if (tid == 0) flag_add(F_O + rb * 3 + 2);
    }
}

typedef CUresult (*EncodeFn)(CUtensorMap*, CUtensorMapDataType, cuuint32_t, void*, const cuuint64_t*, const cuuint64_t*, const cuuint32_t*,
                             const cuuint32_t*, CUtensorMapInterleave, CUtensorMapSwizzle, CUtensorMapL2promotion, CUtensorMapFloatOOBfill);

void make_map(EncodeFn fn, CUtensorMap* m, const void* ptr, uint64_t cols, uint64_t rows, uint32_t bc, uint32_t br, CUtensorMapSwizzle sw) {
    cuuint64_t dims[2] = {cols, rows}, strides[1] = {cols * 2};
    cuuint32_t box[2] = {bc, br}, es[2] = {1, 1};
    fn(m, CU_TENSOR_MAP_DATA_TYPE_BFLOAT16, 2, const_cast<void*>(ptr), dims, strides, box, es, CU_TENSOR_MAP_INTERLEAVE_NONE, sw,
       CU_TENSOR_MAP_L2_PROMOTION_L2_128B, CU_TENSOR_MAP_FLOAT_OOB_FILL_NONE);
}

void make_map3(EncodeFn fn, CUtensorMap* m, const void* ptr, uint64_t cols, uint64_t rows, uint32_t natoms) {
    cuuint64_t dims[3] = {32, rows, cols / 32}, strides[2] = {cols * 2, 64};
    cuuint32_t box[3] = {32, 32, natoms}, es[3] = {1, 1, 1};
    fn(m, CU_TENSOR_MAP_DATA_TYPE_BFLOAT16, 3, const_cast<void*>(ptr), dims, strides, box, es, CU_TENSOR_MAP_INTERLEAVE_NONE, CU_TENSOR_MAP_SWIZZLE_64B,
       CU_TENSOR_MAP_L2_PROMOTION_L2_128B, CU_TENSOR_MAP_FLOAT_OOB_FILL_NONE);
}

}

extern "C" void kernel_launch(void* const* d_in, const int* in_sizes, int n_in, void* d_out, int out_size) {
    static EncodeFn fn = nullptr;
    if (!fn) {
        cudaDriverEntryPointQueryResult qr;
        void* f = nullptr;
        cudaGetDriverEntryPoint("cuTensorMapEncodeTiled", &f, cudaEnableDefault, &qr);
        fn = (EncodeFn)f;
        cudaFuncSetAttribute(mega_kernel, cudaFuncAttributeMaxDynamicSharedMemorySize, SM_TOTAL);
    }
    Params p;
    const __nv_bfloat16* x = (const __nv_bfloat16*)d_in[0];
    make_map(fn, &p.mx, x, DM, S_LEN, 64, 64, CU_TENSOR_MAP_SWIZZLE_128B);
    make_map(fn, &p.mwsp, d_in[7], S_LEN, S_LEN, 64, 64, CU_TENSOR_MAP_SWIZZLE_128B);
    make_map3(fn, &p.mwq, d_in[1], DM, DM, 5);
    make_map3(fn, &p.mwin, d_in[6], 2 * FH, DM, 7);
    p.wq = (const __nv_bfloat16*)d_in[1];
    p.win = (const __nv_bfloat16*)d_in[6];
    p.wk = (const __nv_bfloat16*)d_in[2];
    p.wv = (const __nv_bfloat16*)d_in[3];
    p.bsp = (const __nv_bfloat16*)d_in[8];
    p.gw = (const __nv_bfloat16*)d_in[10];
    p.wo = (const __nv_bfloat16*)d_in[4];
    p.wout = (const __nv_bfloat16*)d_in[9];
    p.out = (__nv_bfloat16*)d_out;
    mega_kernel<<<NCTA, 640, SM_TOTAL>>>(p);
}
```
